```python
import torch

def _softmax(x, axis=-1):
    return torch.softmax(x, dim=axis)
def _gelu(x):
    return torch.nn.functional.gelu(x, approximate="tanh")
def _silu(x):
    return torch.nn.functional.silu(x)
def _sigmoid(x):
    return torch.sigmoid(x)
def _layernorm(x, axis=-1, eps=1e-5):
    m = x.mean(dim=axis, keepdim=True)
    v = x.var(dim=axis, keepdim=True, unbiased=False)
    return (x - m) / torch.sqrt(v + eps)
def _scatter_add(tgt, idx, src, axis=0):
    return tgt.clone().index_add_(axis, idx, src)
def _segment_sum(src, seg, n):
    out = torch.zeros((n,) + src.shape[1:], dtype=src.dtype)
    return out.index_add_(0, seg, src)
def _pad(x, pw):
    flat = tuple(v for pair in reversed(pw) for v in pair)
    return torch.nn.functional.pad(x, flat)

kernel_name = 'standalone__modern_conv_block_convnext__vision'

def setup_inputs():

    _w = (lambda a: (lambda t: t.to(torch.bfloat16) if t.is_floating_point() else t)(torch.as_tensor(a)))
    H = W = 512
    C = 96
    K = 3
    return {
        "x": _w((lambda *s: torch.randn(*s, dtype=torch.bfloat16) * 0.05)(1, H, W, C)),
        "dw": _w((lambda *s: torch.randn(*s, dtype=torch.bfloat16) * 0.05)(K, K, C)),
        "w1": _w((lambda *s: torch.randn(*s, dtype=torch.bfloat16) * 0.05)(C, 4 * C)),
        "b1": _w((lambda *s: torch.randn(*s, dtype=torch.bfloat16) * 0.2)(4 * C)),
        "w2": _w((lambda *s: torch.randn(*s, dtype=torch.bfloat16) * 0.05)(4 * C, C)),
        "b2": _w((lambda *s: torch.randn(*s, dtype=torch.bfloat16) * 0.2)(C)),
        "gamma": _w((lambda *s: torch.randn(*s, dtype=torch.bfloat16) * 0.05)(C)),
    }

def reference(x, dw, w1, b1, w2, b2, gamma):
    B, H, W, C = x.shape
    K = dw.shape[0]
    pad = K // 2
    xp = _pad(x, ((0,0),(pad,pad),(pad,pad),(0,0)))
    out = torch.zeros_like(x)
    for i in range(K):
        for j in range(K):
            out = out + xp[:, i:i+H, j:j+W, :] * dw[i, j][None, None, None, :]
    h = _layernorm(out, axis=-1)
    h = torch.einsum('bhwc,ce->bhwe', h, w1) + b1
    h = _gelu(h)
    h = torch.einsum('bhwe,ec->bhwc', h, w2) + b2
    return x + gamma[None, None, None, :] * h
```

```cpp
#include <cuda_runtime.h>
#include <cuda_bf16.h>
#include <cuda.h>
#include <stdint.h>

namespace {

constexpr int IMG_H = 512, IMG_W = 512, CH = 96, HID = 384;
constexpr int STRIP_W = 64;
constexpr int NUM_STRIPS = IMG_W / STRIP_W;
constexpr int ROWS_PER_CTA = 32;
constexpr int NUM_CTAS = NUM_STRIPS * (IMG_H / ROWS_PER_CTA);
constexpr int HALF_W = STRIP_W / 2 + 3;
constexpr int HALF_BYTES = HALF_W * CH * 2;
constexpr int HALF_BOX = ((HALF_BYTES + 127) / 128) * 128;
constexpr int HALF_OFF = HALF_BOX + CH * 2;
constexpr int ROW_BYTES = 2 * HALF_BOX;
constexpr int NROW = 4;
#define RMLP 128
#define RCONV (512 - 3 * RMLP)
#define ORDER "Ad012b3"
#define NROW0 1
#define NROW1 3
#define PF0 0
constexpr int NA = 2;
constexpr int A_PITCH = CH * 2 + 16;
constexpr int A_HALF = 32 * A_PITCH + 64;
constexpr int A_BYTES = ((A_HALF + 32 * A_PITCH + 127) / 128) * 128;
constexpr int NCH = 64;
constexpr int NCHUNK = HID / NCH;
#define SPLIT_ 2
#define PSPLIT 11
#define FSPLIT 10
constexpr int SPLIT = SPLIT_;
constexpr int NMLP = 3;

constexpr int OFF_W1 = 0;
constexpr int OFF_W2 = OFF_W1 + CH * HID * 2;
constexpr int OFF_ROW = OFF_W2 + CH * HID * 2;
constexpr int OFF_A = OFF_ROW + NROW * ROW_BYTES;
constexpr int OFF_ONES = OFF_A + NA * A_BYTES;
constexpr int OFF_B2I = OFF_ONES + 512;
constexpr int OFF_MAX = OFF_B2I + 384;
constexpr int OFF_DW = OFF_MAX + 128;
constexpr int OFF_BAR = OFF_DW + 9 * CH * 2;
constexpr int BAR_ROW_FULL = 0, BAR_DONE = NROW, BAR_PRIME = BAR_DONE + 4, BAR_A_EMPTY = BAR_PRIME + 1;
constexpr int BAR_W1 = BAR_A_EMPTY + NA, BAR_W2 = BAR_W1 + NCHUNK, BAR_DW = BAR_W2 + NCHUNK;
constexpr int NUM_BARS = BAR_DW + 1;
constexpr int SMEM_BYTES = OFF_BAR + NUM_BARS * 8;
static_assert(SMEM_BYTES <= 232448, "smem");
static_assert(HALF_OFF % 128 == 64 && OFF_ROW % 128 == 0 && OFF_ONES % 128 == 0, "bank layout");

constexpr int NUM_THREADS = 128 * (NMLP + 1);

constexpr float GELU_A = 0.7978845608028654f / 2.423828125f;
constexpr float GELU_INV2A = 0.5f / GELU_A;

__device__ __forceinline__ uint32_t smem_u32(const void* p) { return (uint32_t)__cvta_generic_to_shared(p); }

__device__ __forceinline__ void mbar_init(uint32_t bar, uint32_t count) {
    asm volatile("mbarrier.init.shared::cta.b64 [%0], %1;" ::"r"(bar), "r"(count) : "memory");
}
__device__ __forceinline__ void mbar_expect_tx(uint32_t bar, uint32_t bytes) {
    asm volatile("mbarrier.arrive.expect_tx.shared::cta.b64 _, [%0], %1;" ::"r"(bar), "r"(bytes) : "memory");
}
__device__ __forceinline__ void mbar_arrive(uint32_t bar) {
    asm volatile("mbarrier.arrive.shared::cta.b64 _, [%0];" ::"r"(bar) : "memory");
}
__device__ __forceinline__ bool mbar_try(uint32_t bar, uint32_t parity) {
    uint32_t done;
    asm volatile(
        "{\n\t.reg .pred p;\n\t"
        "mbarrier.try_wait.parity.shared::cta.b64 p, [%1], %2;\n\t"
        "selp.u32 %0, 1, 0, p;\n\t}"
        : "=r"(done) : "r"(bar), "r"(parity) : "memory");
    return done != 0;
}
__device__ __forceinline__ bool mbar_test(uint32_t bar, uint32_t parity) {
    uint32_t done;
    asm volatile(
        "{\n\t.reg .pred p;\n\t"
        "mbarrier.test_wait.parity.shared::cta.b64 p, [%1], %2;\n\t"
        "selp.u32 %0, 1, 0, p;\n\t}"
        : "=r"(done) : "r"(bar), "r"(parity) : "memory");
    return done != 0;
}
__device__ __forceinline__ void mbar_wait(uint32_t bar, uint32_t parity) {
    for (int it = 0; it < (1 << 20); ++it)
        if (mbar_try(bar, parity)) break;
}
__device__ __forceinline__ uint64_t policy_evict_first() {
    uint64_t p;
    asm("createpolicy.fractional.L2::evict_first.b64 %0, 1.0;" : "=l"(p));
    return p;
}
__device__ __forceinline__ void tma_load_3d(uint32_t dst, const CUtensorMap* map, uint32_t bar, int c0, int c1, int c2) {
    asm volatile(
        "cp.async.bulk.tensor.3d.shared::cluster.global.mbarrier::complete_tx::bytes.L2::cache_hint [%0], [%1, {%3, %4, %5}], [%2], %6;"
        ::"r"(dst), "l"(reinterpret_cast<uint64_t>(map)), "r"(bar), "r"(c0), "r"(c1), "r"(c2), "l"(policy_evict_first()) : "memory");
}
__device__ __forceinline__ void tma_load_2d(uint32_t dst, const CUtensorMap* map, uint32_t bar, int c0, int c1) {
    asm volatile(
        "cp.async.bulk.tensor.2d.shared::cluster.global.mbarrier::complete_tx::bytes [%0], [%1, {%3, %4}], [%2];"
        ::"r"(dst), "l"(reinterpret_cast<uint64_t>(map)), "r"(bar), "r"(c0), "r"(c1) : "memory");
}
__device__ __forceinline__ bool elect_one() {
    uint32_t p;
    asm volatile("{\n\t.reg .pred p;\n\telect.sync _|p, 0xffffffff;\n\tselp.u32 %0, 1, 0, p;\n\t}" : "=r"(p));
    return p != 0;
}
__device__ __forceinline__ void bulk_load(uint32_t dst, const void* src, uint32_t bytes, uint32_t bar) {
    asm volatile("cp.async.bulk.shared::cluster.global.mbarrier::complete_tx::bytes [%0], [%1], %2, [%3];"
                 ::"r"(dst), "l"(src), "r"(bytes), "r"(bar) : "memory");
}
__device__ __forceinline__ void bulk_store(void* dst, uint32_t src, uint32_t bytes) {
    asm volatile("cp.async.bulk.global.shared::cta.bulk_group [%0], [%1], %2;" ::"l"(dst), "r"(src), "r"(bytes) : "memory");
}
__device__ __forceinline__ void bulk_commit() { asm volatile("cp.async.bulk.commit_group;" ::: "memory"); }
template <int N> __device__ __forceinline__ void bulk_wait_read() {
    asm volatile("cp.async.bulk.wait_group.read %0;" ::"n"(N) : "memory");
}
template <int N> __device__ __forceinline__ void bulk_wait() {
    asm volatile("cp.async.bulk.wait_group %0;" ::"n"(N) : "memory");
}
__device__ __forceinline__ void ldsm_x4(uint32_t addr, uint32_t& r0, uint32_t& r1, uint32_t& r2, uint32_t& r3) {
    asm volatile("ldmatrix.sync.aligned.m8n8.x4.shared.b16 {%0,%1,%2,%3}, [%4];"
                 : "=r"(r0), "=r"(r1), "=r"(r2), "=r"(r3) : "r"(addr) : "memory");
}
__device__ __forceinline__ void ldsm_x2(uint32_t addr, uint32_t& r0, uint32_t& r1) {
    asm volatile("ldmatrix.sync.aligned.m8n8.x2.shared.b16 {%0,%1}, [%2];" : "=r"(r0), "=r"(r1) : "r"(addr) : "memory");
}
__device__ __forceinline__ void stsm_x4(uint32_t addr, uint32_t r0, uint32_t r1, uint32_t r2, uint32_t r3) {
    asm volatile("stmatrix.sync.aligned.m8n8.x4.shared.b16 [%0], {%1,%2,%3,%4};"
                 ::"r"(addr), "r"(r0), "r"(r1), "r"(r2), "r"(r3) : "memory");
}
__device__ __forceinline__ uint4 lds128(uint32_t addr) {
    uint4 v;
    asm volatile("ld.shared.v4.u32 {%0,%1,%2,%3}, [%4];" : "=r"(v.x), "=r"(v.y), "=r"(v.z), "=r"(v.w) : "r"(addr) : "memory");
    return v;
}
__device__ __forceinline__ uint32_t lds32(uint32_t addr) {
    uint32_t a;
    asm volatile("ld.shared.u32 %0, [%1];" : "=r"(a) : "r"(addr) : "memory");
    return a;
}
__device__ __forceinline__ void sts32(uint32_t addr, uint32_t a) {
    asm volatile("st.shared.u32 [%0], %1;" ::"r"(addr), "r"(a) : "memory");
}
__device__ __forceinline__ void sts128(uint32_t addr, uint32_t a, uint32_t b, uint32_t c, uint32_t d) {
    asm volatile("st.shared.v4.u32 [%0], {%1,%2,%3,%4};" ::"r"(addr), "r"(a), "r"(b), "r"(c), "r"(d) : "memory");
}
__device__ __forceinline__ uint32_t hfma2_bf16(uint32_t a, uint32_t b, uint32_t c) {
    uint32_t d;
    asm("fma.rn.bf16x2 %0, %1, %2, %3;" : "=r"(d) : "r"(a), "r"(b), "r"(c));
    return d;
}
__device__ __forceinline__ uint32_t hmul2_bf16(uint32_t a, uint32_t b) {
    uint32_t d;
    asm("mul.rn.bf16x2 %0, %1, %2;" : "=r"(d) : "r"(a), "r"(b));
    return d;
}
__device__ __forceinline__ uint32_t hadd2_bf16(uint32_t a, uint32_t b) {
    uint32_t d;
    asm("add.rn.bf16x2 %0, %1, %2;" : "=r"(d) : "r"(a), "r"(b));
    return d;
}
__device__ __forceinline__ float bf_lo(uint32_t v) { return __uint_as_float(v << 16); }
__device__ __forceinline__ float bf_hi(uint32_t v) { return __uint_as_float(v & 0xffff0000u); }
__device__ __forceinline__ uint32_t pack_bf16(float lo, float hi) {
    uint32_t d;
    asm("cvt.rn.bf16x2.f32 %0, %1, %2;" : "=r"(d) : "f"(hi), "f"(lo));
    return d;
}
__device__ __forceinline__ uint32_t pack_f16(float lo, float hi) {
    uint32_t d;
    asm("cvt.rn.f16x2.f32 %0, %1, %2;" : "=r"(d) : "f"(hi), "f"(lo));
    return d;
}
__device__ __forceinline__ uint32_t scale2h(uint32_t v, float s) {
    return pack_f16(bf_lo(v) * s, bf_hi(v) * s);
}
__device__ __forceinline__ uint32_t h2_to_bf2(uint32_t v) {
    uint32_t d;
    asm("{\n\t.reg .b16 l, h;\n\t.reg .f32 a, b;\n\tmov.b32 {l, h}, %1;\n\tcvt.f32.f16 a, l;\n\tcvt.f32.f16 b, h;\n\t"
        "cvt.rn.bf16x2.f32 %0, b, a;\n\t}" : "=r"(d) : "r"(v));
    return d;
}
__device__ __forceinline__ uint32_t hsub2_f16(uint32_t a, uint32_t b) {
    uint32_t d;
    asm("sub.rn.f16x2 %0, %1, %2;" : "=r"(d) : "r"(a), "r"(b));
    return d;
}
__device__ __forceinline__ uint32_t hmul2_f16(uint32_t a, uint32_t b) {
    uint32_t d;
    asm("mul.rn.f16x2 %0, %1, %2;" : "=r"(d) : "r"(a), "r"(b));
    return d;
}
__device__ __forceinline__ uint32_t bf2_to_h2(uint32_t y) { return (y & 0x7fff7fffu) * 7u + y; }
__device__ __forceinline__ uint32_t absmax2(uint32_t m, uint32_t v) { return __vmaxu2(m, v & 0x7fff7fffu); }
__device__ __forceinline__ void red_add_bf16x8(void* p, uint32_t a, uint32_t b, uint32_t c, uint32_t d) {
    asm volatile("red.global.add.noftz.v4.bf16x2 [%0], {%1,%2,%3,%4};" ::"l"(p), "r"(a), "r"(b), "r"(c), "r"(d) : "memory");
}
__device__ __forceinline__ uint32_t gelu2x(uint32_t v) {
    uint32_t p, z, t, g;
    asm("fma.rn.f16x2 %0, %1, %1, %2;" : "=r"(p) : "r"(v), "r"(0x40D940D9u));
    asm("mul.rn.f16x2 %0, %1, %2;" : "=r"(z) : "r"(v), "r"(p));
    asm("tanh.approx.f16x2 %0, %1;" : "=r"(t) : "r"(z));
    asm("fma.rn.f16x2 %0, %1, %2, %1;" : "=r"(g) : "r"(v), "r"(t));
    return g;
}
__device__ __forceinline__ void wg_fence() { asm volatile("wgmma.fence.sync.aligned;" ::: "memory"); }
__device__ __forceinline__ void wg_commit() { asm volatile("wgmma.commit_group.sync.aligned;" ::: "memory"); }
template <int N> __device__ __forceinline__ void wg_wait() {
    asm volatile("wgmma.wait_group.sync.aligned %0;" ::"n"(N) : "memory");
}
template <int N> __device__ __forceinline__ void fence_regs(float (&d)[N]) {
#pragma unroll
    for (int i = 0; i < N; ++i) asm volatile("" : "+f"(d[i])::"memory");
}
template <int N> __device__ __forceinline__ void fence_regs(uint32_t (&d)[N]) {
#pragma unroll
    for (int i = 0; i < N; ++i) asm volatile("" : "+r"(d[i])::"memory");
}

template <int N> struct WH;
template <> struct WH<64> {
    static __device__ __forceinline__ void acc(uint32_t* d, uint32_t a0, uint32_t a1, uint32_t a2, uint32_t a3, uint64_t desc) {
        asm volatile("wgmma.mma_async.sync.aligned.m64n64k16.f16.f16.f16 {%0,%1,%2,%3,%4,%5,%6,%7,%8,%9,%10,%11,%12,%13,%14,%15}, "
                     "{%16,%17,%18,%19}, %20, 1, 1, 1, 1;"
                     : "+r"(d[0]), "+r"(d[1]), "+r"(d[2]), "+r"(d[3]), "+r"(d[4]), "+r"(d[5]), "+r"(d[6]), "+r"(d[7]), "+r"(d[8]), "+r"(d[9]), "+r"(d[10]), "+r"(d[11]), "+r"(d[12]), "+r"(d[13]), "+r"(d[14]), "+r"(d[15])
                     : "r"(a0), "r"(a1), "r"(a2), "r"(a3), "l"(desc) : "memory");
    }
    static __device__ __forceinline__ void first(uint32_t* d, uint32_t a0, uint32_t a1, uint32_t a2, uint32_t a3, uint64_t desc) {
        asm volatile("wgmma.mma_async.sync.aligned.m64n64k16.f16.f16.f16 {%0,%1,%2,%3,%4,%5,%6,%7,%8,%9,%10,%11,%12,%13,%14,%15}, "
                     "{%16,%17,%18,%19}, %20, 0, 1, 1, 1;"
                     : "=r"(d[0]), "=r"(d[1]), "=r"(d[2]), "=r"(d[3]), "=r"(d[4]), "=r"(d[5]), "=r"(d[6]), "=r"(d[7]), "=r"(d[8]), "=r"(d[9]), "=r"(d[10]), "=r"(d[11]), "=r"(d[12]), "=r"(d[13]), "=r"(d[14]), "=r"(d[15])
                     : "r"(a0), "r"(a1), "r"(a2), "r"(a3), "l"(desc) : "memory");
    }
};
template <> struct WH<96> {
    static __device__ __forceinline__ void acc(uint32_t* d, uint32_t a0, uint32_t a1, uint32_t a2, uint32_t a3, uint64_t desc) {
        asm volatile("wgmma.mma_async.sync.aligned.m64n96k16.f16.f16.f16 {%0,%1,%2,%3,%4,%5,%6,%7,%8,%9,%10,%11,%12,%13,%14,%15,%16,%17,%18,%19,%20,%21,%22,%23}, "
                     "{%24,%25,%26,%27}, %28, 1, 1, 1, 1;"
                     : "+r"(d[0]), "+r"(d[1]), "+r"(d[2]), "+r"(d[3]), "+r"(d[4]), "+r"(d[5]), "+r"(d[6]), "+r"(d[7]), "+r"(d[8]), "+r"(d[9]), "+r"(d[10]), "+r"(d[11]), "+r"(d[12]), "+r"(d[13]), "+r"(d[14]), "+r"(d[15]), "+r"(d[16]), "+r"(d[17]), "+r"(d[18]), "+r"(d[19]), "+r"(d[20]), "+r"(d[21]), "+r"(d[22]), "+r"(d[23])
                     : "r"(a0), "r"(a1), "r"(a2), "r"(a3), "l"(desc) : "memory");
    }
    static __device__ __forceinline__ void first(uint32_t* d, uint32_t a0, uint32_t a1, uint32_t a2, uint32_t a3, uint64_t desc) {
        asm volatile("wgmma.mma_async.sync.aligned.m64n96k16.f16.f16.f16 {%0,%1,%2,%3,%4,%5,%6,%7,%8,%9,%10,%11,%12,%13,%14,%15,%16,%17,%18,%19,%20,%21,%22,%23}, "
                     "{%24,%25,%26,%27}, %28, 0, 1, 1, 1;"
                     : "=r"(d[0]), "=r"(d[1]), "=r"(d[2]), "=r"(d[3]), "=r"(d[4]), "=r"(d[5]), "=r"(d[6]), "=r"(d[7]), "=r"(d[8]), "=r"(d[9]), "=r"(d[10]), "=r"(d[11]), "=r"(d[12]), "=r"(d[13]), "=r"(d[14]), "=r"(d[15]), "=r"(d[16]), "=r"(d[17]), "=r"(d[18]), "=r"(d[19]), "=r"(d[20]), "=r"(d[21]), "=r"(d[22]), "=r"(d[23])
                     : "r"(a0), "r"(a1), "r"(a2), "r"(a3), "l"(desc) : "memory");
    }
};

__device__ __forceinline__ void wgmma_stat_first(float (&d)[4], const uint32_t (&a)[4], uint64_t desc) {
    asm volatile("wgmma.mma_async.sync.aligned.m64n8k16.f32.bf16.bf16 {%0,%1,%2,%3}, {%4,%5,%6,%7}, %8, 0, 1, 1, 1;"
                 : "=f"(d[0]), "=f"(d[1]), "=f"(d[2]), "=f"(d[3]) : "r"(a[0]), "r"(a[1]), "r"(a[2]), "r"(a[3]), "l"(desc) : "memory");
}
__device__ __forceinline__ void wgmma_stat_acc(float (&d)[4], const uint32_t (&a)[4], uint64_t desc) {
    asm volatile("wgmma.mma_async.sync.aligned.m64n8k16.f32.bf16.bf16 {%0,%1,%2,%3}, {%4,%5,%6,%7}, %8, 1, 1, 1, 1;"
                 : "+f"(d[0]), "+f"(d[1]), "+f"(d[2]), "+f"(d[3]) : "r"(a[0]), "r"(a[1]), "r"(a[2]), "r"(a[3]), "l"(desc) : "memory");
}

__device__ __forceinline__ uint64_t make_desc(uint32_t addr, uint32_t lbo, uint32_t sbo) {
    return (uint64_t)((addr & 0x3FFFF) >> 4) | ((uint64_t)(lbo >> 4) << 16) | ((uint64_t)(sbo >> 4) << 32);
}

#define CK_BEGIN()
#define CK_END()
#define TL(slot)

#define SCHED_FENCE() asm volatile("{\n\t.reg .pred p;\n\tsetp.ne.u32 p, %0, 0;\n\t@p exit;\n\t}" ::"r"(zero) : "memory")

__global__ void __launch_bounds__(NUM_THREADS, 1)
convnext_fused_kernel(const __grid_constant__ CUtensorMap xmap, const __grid_constant__ CUtensorMap w1map,
                      const __nv_bfloat16* __restrict__ dw, const __nv_bfloat16* __restrict__ w1,
                      const __nv_bfloat16* __restrict__ b1, const __nv_bfloat16* __restrict__ w2,
                      const __nv_bfloat16* __restrict__ b2, const __nv_bfloat16* __restrict__ gamma,
                      __nv_bfloat16* __restrict__ out, uint32_t zero) {
    extern __shared__ __align__(1024) uint8_t smem[];
    const uint32_t sbase = smem_u32(smem);
    const int tid = threadIdx.x;
    const int warp = __shfl_sync(0xffffffffu, tid >> 5, 0);
    const int lane = tid & 31;
    const int wg = warp >> 2, wr = warp & 3;
    const uint32_t bars = sbase + OFF_BAR;
    const int strip = blockIdx.x % NUM_STRIPS;
    const int band = blockIdx.x / NUM_STRIPS;
    const int dir = (band & 1) ? 1 : -1;
    const int ys = (band & 1) ? band * ROWS_PER_CTA - 1 : (band + 1) * ROWS_PER_CTA;
    TL(0);
    CK_BEGIN();

    auto load_row = [&](int j) {
        const uint32_t bar = bars + 8 * (BAR_ROW_FULL + (j & 3));
        const uint32_t dst = sbase + OFF_ROW + (j & 3) * ROW_BYTES;
        mbar_expect_tx(bar, 2 * HALF_BYTES);
        tma_load_3d(dst, &xmap, bar, 0, strip * STRIP_W - 1, ys + dir * j);
        tma_load_3d(dst + HALF_BOX, &xmap, bar, 0, strip * STRIP_W + 30, ys + dir * j);
    };
    if (warp == 11) {
        if (elect_one()) {
            for (int s = 0; s < NUM_BARS; ++s) mbar_init(bars + 8 * s, (s >= BAR_DONE && s < BAR_W1) ? 4 : 1);
            asm volatile("fence.mbarrier_init.release.cluster;" ::: "memory");
        }
        __syncwarp();
        asm volatile("bar.arrive 2, %0;" ::"n"(NUM_THREADS) : "memory");
        if (elect_one()) {
            constexpr char order[] = ORDER;
#pragma unroll
            for (int i = 0; i < 7; ++i) {
                if (order[i] == 'A') {
#pragma unroll 1
                    for (int s = 0; s < NCHUNK; ++s) {
                        mbar_expect_tx(bars + 8 * (BAR_W1 + s), CH * NCH * 2);
                        tma_load_2d(sbase + OFF_W1 + s * (CH * NCH * 2), &w1map, bars + 8 * (BAR_W1 + s), s * NCH, 0);
                    }
                } else if (order[i] == 'b') {
#pragma unroll 1
                    for (int s = 0; s < NCHUNK; ++s) {
                        mbar_expect_tx(bars + 8 * (BAR_W2 + s), CH * NCH * 2);
                        bulk_load(sbase + OFF_W2 + s * (CH * NCH * 2), w2 + s * (CH * NCH), CH * NCH * 2, bars + 8 * (BAR_W2 + s));
                    }
                } else if (order[i] == 'd') {
                    mbar_expect_tx(bars + 8 * BAR_DW, 9 * CH * 2);
                    bulk_load(sbase + OFF_DW, dw, 9 * CH * 2, bars + 8 * BAR_DW);
                } else {
                    load_row(order[i] - '0');
                }
            }
        }
        __syncwarp();
    } else if (warp == 10) {
        if (elect_one()) asm volatile("prefetch.tensormap [%0];" ::"l"(reinterpret_cast<uint64_t>(&xmap)) : "memory");
    }
    TL(80);

    if (wg == NMLP) {
        asm volatile("setmaxnreg.dec.sync.aligned.u32 %0;" ::"n"(RCONV));
        asm volatile("bar.sync 2, %0;" ::"n"(NUM_THREADS) : "memory");
        uint32_t w[3][3][3];
        {
            mbar_wait(bars + 8 * BAR_DW, 0);
            const uint32_t wp = sbase + OFF_DW + 48 * ((wr + (lane >> 2)) & 3) + 4 * (lane & 3) + 3 * (CH * 2);
#pragma unroll
            for (int s = 0; s < 3; ++s)
#pragma unroll
                for (int t = 0; t < 9; ++t) w[t / 3][t % 3][s] = lds32(wp + (t / 3 - 1) * dir * 3 * (CH * 2) + (t % 3) * (CH * 2) + s * 16);
        }
        const int ga = lane & 7, ja = lane >> 3;
        const uint32_t ip = sbase + OFF_ROW + (uint32_t)((ga >> 2) * HALF_OFF + (8 * (ga & 3) + ja) * (CH * 2) + 48 * ((wr + ga) & 3));
        const uint32_t op = sbase + OFF_A + (uint32_t)((ga >> 2) * A_HALF + (8 * (ga & 3) + ja) * A_PITCH + 48 * ((wr + ga) & 3));
        static_assert(NROW == 4 && NA == 2, "ring arithmetic");
        uint32_t P[2][3][8], f[10], c[8];
        auto feed = [&](int e, int s, int i) {
#pragma unroll
            for (int o = i - 2; o <= i; ++o) {
                if (o < 0 || o > 7) continue;
                const int jx = i - o;
                if (jx == 0) {
                    asm volatile("fma.rn.bf16x2 %0, %3, %4, %1;\n\tfma.rn.bf16x2 %2, %3, %5, %2;\n\tmul.rn.bf16x2 %1, %3, %6;"
                                 : "=&r"(c[o]), "+r"(P[e][s][o]), "+r"(P[e ^ 1][s][o])
                                 : "r"(f[i]), "r"(w[2][0][s]), "r"(w[1][0][s]), "r"(w[0][0][s]));
                } else {
                    asm volatile("fma.rn.bf16x2 %0, %3, %4, %0;\n\tfma.rn.bf16x2 %2, %3, %5, %2;\n\tfma.rn.bf16x2 %1, %3, %6, %1;"
                                 : "+r"(c[o]), "+r"(P[e][s][o]), "+r"(P[e ^ 1][s][o])
                                 : "r"(f[i]), "r"(w[2][jx][s]), "r"(w[1][jx][s]), "r"(w[0][jx][s]));
                }
            }
        };
        constexpr int NSTEPS = ROWS_PER_CTA + 2;
        __nv_bfloat16* xo = out + ((ys + dir) * IMG_W + strip * STRIP_W + wr * 16) * CH;
        const uint32_t xs = sbase + OFF_ROW + (wr >> 1) * HALF_OFF + ((wr & 1) * 16 + 1) * (CH * 2);
        mbar_wait(bars + 8 * BAR_ROW_FULL, 0);
        TL(4);
#pragma unroll
        for (int r = 0; r < 2; ++r) {
            if (r == 1) {
                mbar_wait(bars + 8 * (BAR_ROW_FULL + 1), 0);
                if (elect_one()) {
                    bulk_store(xo, xs + ROW_BYTES, 16 * CH * 2);
                    bulk_commit();
                }
            }
#pragma unroll
            for (int s = 0; s < 3; ++s) {
                ldsm_x4(ip + r * ROW_BYTES + s * 16, f[0], f[1], f[2], f[3]);
                ldsm_x4(ip + r * ROW_BYTES + s * 16 + 4 * (CH * 2), f[4], f[5], f[6], f[7]);
                ldsm_x2(ip + r * ROW_BYTES + s * 16 + 8 * (CH * 2), f[8], f[9]);
#pragma unroll
                for (int o = 0; o < 8; ++o) {
                    if (r == 1) P[0][s][o] = hfma2_bf16(f[o + 2], w[1][2][s], hfma2_bf16(f[o + 1], w[1][1][s], hfma2_bf16(f[o], w[1][0][s], P[0][s][o])));
                    P[r][s][o] = hfma2_bf16(f[o + 2], w[0][2][s], hfma2_bf16(f[o + 1], w[0][1][s], hmul2_bf16(f[o], w[0][0][s])));
                }
            }
        }
        __syncwarp();
        if (elect_one()) {
            bulk_wait_read<0>();
            mbar_arrive(bars + 8 * BAR_PRIME);
        }
        TL(5);
        if (wr < 2) {
            mbar_wait(bars + 8 * BAR_PRIME, 0);
            if (elect_one()) load_row(4 + wr);
        }
        mbar_wait(bars + 8 * (BAR_ROW_FULL + 2), 0);
        TL(6);
        ldsm_x4(ip + 2 * ROW_BYTES, f[0], f[1], f[2], f[3]);
        ldsm_x4(ip + 2 * ROW_BYTES + 4 * (CH * 2), f[4], f[5], f[6], f[7]);
        ldsm_x2(ip + 2 * ROW_BYTES + 8 * (CH * 2), f[8], f[9]);
#pragma unroll 1
        for (int m = 0; m < ROWS_PER_CTA / 4; ++m) {
            const bool last = m + 1 == ROWS_PER_CTA / 4;
#pragma unroll
            for (int u = 0; u < 4; ++u) {
                const int j = 4 * m + u + 2;
                const int rs = (u + 2) & 3, ns = (u + 3) & 3;
                TL(4 + 6 * j + 0);
                const uint32_t ebar = bars + 8 * (BAR_A_EMPTY + (u & 1)), rbar = bars + 8 * (BAR_ROW_FULL + ns);
                const uint32_t eph = ((u >> 1) & 1) ^ 1, rph = (m + (u >= 1)) & 1;
                xo += dir * IMG_W * CH;
                if (!(u == 3 && last)) {
                    if (elect_one()) bulk_store(xo, xs + rs * ROW_BYTES, 16 * CH * 2);
                }
                bulk_commit();
                bool ok = mbar_test(ebar, eph);
#pragma unroll
                for (int s = 0; s < 3; ++s) {
                    if (s == 2) ok = mbar_test(rbar, rph) || (u == 3 && last);
                    feed(u & 1, s, 0); feed(u & 1, s, 1); feed(u & 1, s, 2); feed(u & 1, s, 3);
                    if (s == 0) {
                        if (!ok) mbar_wait(ebar, eph);
                        TL(4 + 6 * j + 1);
                        if (wr == u && (u < 2 ? m > 0 : !last)) {
                            if (elect_one()) load_row(j + 2);
                        }
                    }
                    if (s == 2) {
                        if (!ok) mbar_wait(rbar, rph);
                        TL(4 + 6 * j + 2);
                    }
                    const uint32_t nx = ip + (s == 2 ? ns : rs) * ROW_BYTES + ((s + 1) % 3) * 16;
                    const uint32_t ox = op + (u & 1) * A_BYTES + s * 16;
                    ldsm_x4(nx, f[0], f[1], f[2], f[3]);
                    SCHED_FENCE();
                    feed(u & 1, s, 4); feed(u & 1, s, 5);
                    stsm_x4(ox, c[0], c[1], c[2], c[3]);
                    feed(u & 1, s, 6); feed(u & 1, s, 7);
                    ldsm_x4(nx + 4 * (CH * 2), f[4], f[5], f[6], f[7]);
                    SCHED_FENCE();
                    feed(u & 1, s, 8); feed(u & 1, s, 9);
                    stsm_x4(ox + 4 * A_PITCH, c[4], c[5], c[6], c[7]);
                    ldsm_x2(nx + 8 * (CH * 2), f[8], f[9]);
                    SCHED_FENCE();
                }
                TL(4 + 6 * j + 4);
                bulk_wait<0>();
                __syncwarp();
                if (elect_one()) mbar_arrive(bars + 8 * (BAR_DONE + u));
                TL(4 + 6 * j + 5);
            }
        }
    } else {
        const int g = lane >> 2, q = lane & 3;
        uint4 r95, bb, gm[3];
        uint32_t b2v = 0, g2v = 0;
        r95 = __ldg(reinterpret_cast<const uint4*>(w1 + 95 * HID + (warp >> 1) * NCH + (lane & 7) * 8));
        bb = __ldg(reinterpret_cast<const uint4*>(b1 + (warp >> 1) * NCH + (lane & 7) * 8));
#pragma unroll
        for (int jj = 0; jj < 3; ++jj) gm[jj] = __ldg(reinterpret_cast<const uint4*>(gamma + jj * 32 + q * 8));
        if (tid < CH / 2) {
            b2v = __ldg(reinterpret_cast<const uint32_t*>(b2) + tid);
            g2v = __ldg(reinterpret_cast<const uint32_t*>(gamma) + tid);
        }
        if (warp != 11) asm volatile("bar.sync 2, %0;" ::"n"(NUM_THREADS) : "memory");
        TL(82);
        asm volatile("setmaxnreg.inc.sync.aligned.u32 %0;" ::"n"(RMLP));
        uint32_t oscale;
        {
            const int box = warp >> 1, cc = lane & 7, k0 = (warp & 1) * 48 + (lane >> 3);
            constexpr uint32_t DN = 0x07800780u;
            TL(3);
            if (warp == 0) {
                sts128(sbase + OFF_ONES + lane * 16, lane < 16 ? 0x3F80u : 0x3F800000u, lane < 16 ? 0x3F80u : 0x3F800000u,
                       lane < 16 ? 0x3F80u : 0x3F800000u, lane < 16 ? 0x3F80u : 0x3F800000u);
            }
            const uint32_t m[4] = {scale2h(r95.x, 1.f), scale2h(r95.y, 1.f), scale2h(r95.z, 1.f), scale2h(r95.w, 1.f)};
            const uint32_t tb[4] = {scale2h(bb.x, GELU_A), scale2h(bb.y, GELU_A), scale2h(bb.z, GELU_A), scale2h(bb.w, GELU_A)};
            uint32_t mx = absmax2(absmax2(absmax2(absmax2(0, hmul2_bf16(bb.x, DN)), hmul2_bf16(bb.y, DN)), hmul2_bf16(bb.z, DN)), hmul2_bf16(bb.w, DN));
            uint32_t mg = 0;
#pragma unroll
            for (int jj = 0; jj < 3; ++jj) mg = absmax2(absmax2(absmax2(absmax2(mg, gm[jj].x), gm[jj].y), gm[jj].z), gm[jj].w);
            mg = __reduce_max_sync(0xffffffffu, max(mg & 0xffffu, mg >> 16));
            if (warp < 2) {
                const uint32_t mb = __reduce_max_sync(0xffffffffu, max(b2v & 0x7fffu, (b2v >> 16) & 0x7fffu));
                if (lane == 0) sts32(sbase + OFF_MAX + 48 + warp * 4, mb);
            }
            const uint32_t wb = sbase + OFF_W1 + box * (CH * NCH * 2);
            const uint32_t a0 = wb + k0 * 128 + ((cc ^ (k0 & 7)) << 4), a1_ = wb + (k0 + 4) * 128 + ((cc ^ ((k0 + 4) & 7)) << 4);
            mbar_wait(bars + 8 * (BAR_W1 + box), 0);
            TL(2);
            uint4 u[2] = {lds128(a0), lds128(a1_)};
#pragma unroll 1
            for (int i = 0; i < 6; ++i) {
                TL(90 + i);
                uint32_t t[2][4];
#pragma unroll
                for (int e = 0; e < 2; ++e) {
                    t[e][0] = hmul2_bf16(u[e].x, DN); t[e][1] = hmul2_bf16(u[e].y, DN); t[e][2] = hmul2_bf16(u[e].z, DN); t[e][3] = hmul2_bf16(u[e].w, DN);
                    if (i < 5) u[e] = lds128((e ? a1_ : a0) + (i + 1) * 1024);
#pragma unroll
                    for (int x = 0; x < 4; ++x) {
                        mx = absmax2(mx, t[e][x]);
                        t[e][x] = hsub2_f16(bf2_to_h2(t[e][x]), m[x]);
                    }
                }
                sts128(a0 + i * 1024, t[0][0], t[0][1], t[0][2], t[0][3]);
                sts128(a1_ + i * 1024, t[1][0], t[1][1], t[1][2], t[1][3]);
            }
            if (k0 + 44 == 95) sts128(a1_ + 5 * 1024, tb[0], tb[1], tb[2], tb[3]);
            const uint32_t m1w = __reduce_max_sync(0xffffffffu, max(mx & 0xffffu, mx >> 16));
            TL(100);
            const uint32_t w2b = sbase + OFF_W2 + warp * 4 * (8 * CH * 2);
            int s = 0, s2 = 0;
#pragma unroll 1
            for (int pass = 0; pass < 2; ++pass) {
                const float sc = __uint_as_float((uint32_t)(127 + s - s2) << 23) * GELU_INV2A;
                const uint32_t dn2 = (uint32_t)(15 + s2) * 0x00800080u;
                uint32_t gs[12];
#pragma unroll
                for (int jj = 0; jj < 3; ++jj) {
                    gs[jj * 4] = scale2h(gm[jj].x, sc); gs[jj * 4 + 1] = scale2h(gm[jj].y, sc);
                    gs[jj * 4 + 2] = scale2h(gm[jj].z, sc); gs[jj * 4 + 3] = scale2h(gm[jj].w, sc);
                }
                mbar_wait(bars + 8 * (BAR_W2 + box), pass);
                TL(101);
                uint4 v[3];
#pragma unroll
                for (int jj = 0; jj < 3; ++jj) v[jj] = lds128(w2b + g * (CH * 2) + jj * 64 + q * 16);
                uint32_t mu = 0, ms = 0;
#pragma unroll 1
                for (int i = 0; i < 4; ++i) {
                    TL(110 + i);
                    uint32_t o[12];
#pragma unroll
                    for (int jj = 0; jj < 3; ++jj) {
                        mu = __vmaxu2(__vmaxu2(mu, v[jj].x), v[jj].y); mu = __vmaxu2(__vmaxu2(mu, v[jj].z), v[jj].w);
                        ms = __vmaxs2(__vmaxs2(ms, v[jj].x), v[jj].y); ms = __vmaxs2(__vmaxs2(ms, v[jj].z), v[jj].w);
                        o[jj * 4 + 0] = hmul2_bf16(v[jj].x, dn2); o[jj * 4 + 1] = hmul2_bf16(v[jj].y, dn2);
                        o[jj * 4 + 2] = hmul2_bf16(v[jj].z, dn2); o[jj * 4 + 3] = hmul2_bf16(v[jj].w, dn2);
                        if (i < 3) v[jj] = lds128(w2b + (i + 1) * (8 * CH * 2) + g * (CH * 2) + jj * 64 + q * 16);
                    }
                    __syncwarp();
#pragma unroll
                    for (int e = 0; e < 12; ++e) o[e] = hmul2_f16(bf2_to_h2(o[e]), gs[e]);
#pragma unroll
                    for (int jj = 0; jj < 3; ++jj)
                        stsm_x4(w2b + i * (8 * CH * 2) + jj * 512 + lane * 16, o[jj * 4], o[jj * 4 + 1], o[jj * 4 + 2], o[jj * 4 + 3]);
                }
                TL(103);
                if (tid < CH / 2) {
                    const float up = __uint_as_float((uint32_t)(127 + s) << 23);
                    const uint32_t v2 = pack_f16(bf_lo(b2v) * bf_lo(g2v) * up, bf_hi(b2v) * bf_hi(g2v) * up);
                    const uint32_t a = sbase + OFF_B2I + ((tid >> 4) * 2 + ((tid >> 1) & 1)) * 64 + ((tid >> 2) & 3) * 16 + (tid & 1) * 8;
                    sts32(a, v2); sts32(a + 4, v2);
                }
                mu = __vmaxu2(mu & 0x7fff7fffu, ms);
                mu = __reduce_max_sync(0xffffffffu, max(mu & 0xffffu, mu >> 16));
                if (lane == 0) sts32(sbase + OFF_MAX + warp * 4, mu | (m1w << 16));
                asm volatile("fence.proxy.async.shared::cta;" ::: "memory");
                asm volatile("bar.sync 1, %0;" ::"n"(NMLP * 128) : "memory");
                if (pass == 1) break;
                const uint32_t mm = lane < 14 ? lds32(sbase + OFF_MAX + lane * 4) : 0;
                const uint32_t m1 = __reduce_max_sync(0xffffffffu, mm >> 16);
                const uint32_t m2 = __reduce_max_sync(0xffffffffu, lane < 12 ? mm & 0xffffu : 0);
                const uint32_t mb = __reduce_max_sync(0xffffffffu, lane < 12 ? 0 : mm);
                const int e1 = max((int)(m1 >> 7), 1) - 13, eg = (int)(mg >> 7) - 126, ew = (int)(m2 >> 7) - 126;
                const int e2 = ew + eg + 1, eb = (int)(mb >> 7) - 126 + eg;
                s = min(min(-1 - e1 - e2, 14 - eb), 14 - e2);
                if (s >= 0 && s <= 12 && e2 >= -9 && ew >= -9 && ew <= 14 && eg >= -9 && eg <= 14) { s = 0; break; }
                s2 = min(max(-ew, -14), 120);
                s = min(max(s, s2 - 120), min(s2 + 120, 120));
                s = max(s, -120);
                if ((warp & 1) == 0 && elect_one()) {
                    mbar_expect_tx(bars + 8 * (BAR_W2 + box), CH * NCH * 2);
                    bulk_load(sbase + OFF_W2 + box * (CH * NCH * 2), w2 + box * (CH * NCH), CH * NCH * 2, bars + 8 * (BAR_W2 + box));
                }
            }
            oscale = (uint32_t)(127 - s) * 0x00800080u;
        }
        TL(1);
        const uint64_t descW1 = make_desc(sbase + OFF_W1, CH * NCH * 2, 1024) | (1ull << 62);
        const uint64_t descW2 = make_desc(sbase + OFF_W2, (CH / 8) * 128, 128);
        const uint64_t descS = make_desc(sbase + OFF_ONES, 128, 128);
        uint32_t la = sbase + OFF_A + (wg & 1) * A_BYTES + wr * 16 * A_PITCH + (wr >> 1) * 64 +
                            (uint32_t)(((lane & 7) + ((lane >> 3) & 1) * 8) * A_PITCH + (lane >> 4) * 16);

        uint32_t acc2[24];
        uint32_t h[2][NCH / 4];
        uint32_t a1[6][4];
        uint32_t ps[4], pq[4];
        float st[4];

        auto load_a = [&]() {
#pragma unroll
            for (int kb = 0; kb < 6; ++kb) ldsm_x4(la + kb * 32, a1[kb][0], a1[kb][1], a1[kb][2], a1[kb][3]);
        };
        auto partial_a = [&]() {
#pragma unroll
            for (int i = 0; i < 4; ++i) {
                ps[i] = hadd2_bf16(hadd2_bf16(hadd2_bf16(a1[0][i], a1[1][i]), hadd2_bf16(a1[2][i], a1[3][i])), hadd2_bf16(a1[4][i], a1[5][i]));
                pq[i] = hmul2_bf16(a1[0][i], a1[0][i]);
#pragma unroll
                for (int kb = 1; kb < 6; ++kb) pq[i] = hfma2_bf16(a1[kb][i], a1[kb][i], pq[i]);
            }
        };
        auto reduce_a = [&]() {
            wgmma_stat_first(st, ps, descS);
            wgmma_stat_acc(st, pq, descS + 16);
        };
        auto norm_a = [&]() {
            float m0 = st[0] * (1.f / CH), m1 = st[2] * (1.f / CH);
            float r0, r1;
            asm("rsqrt.approx.ftz.f32 %0, %1;" : "=f"(r0) : "f"(fmaxf(fmaf(-m0, m0, st[1] * (1.f / CH)), 0.f) + 1e-5f));
            asm("rsqrt.approx.ftz.f32 %0, %1;" : "=f"(r1) : "f"(fmaxf(fmaf(-m1, m1, st[3] * (1.f / CH)), 0.f) + 1e-5f));
            const bool easy = fmaxf(fabsf(m0 * r0), fabsf(m1 * r1)) < 0.5f && fminf(r0, r1) > 0x1p-9f;
            if (__all_sync(0xffffffffu, easy)) {
                constexpr float K = GELU_A * 0x1p-112f;
                const uint32_t rp0 = pack_bf16(r0 * K, r0 * K), rp1 = pack_bf16(r1 * K, r1 * K);
                const float o0 = -m0 * bf_lo(rp0), o1 = -m1 * bf_lo(rp1);
                const uint32_t op0 = pack_bf16(o0, o0), op1 = pack_bf16(o1, o1);
#pragma unroll
                for (int kb = 0; kb < 6; ++kb)
#pragma unroll
                    for (int i = 0; i < 4; ++i) {
                        const uint32_t y = hfma2_bf16(a1[kb][i], (i & 1) ? rp1 : rp0, (i & 1) ? op1 : op0);
                        a1[kb][i] = bf2_to_h2(y);
                    }
            } else {
                float s0[2] = {0.f, 0.f}, s1[2] = {0.f, 0.f}, v0[2] = {0.f, 0.f}, v1[2] = {0.f, 0.f};
#pragma unroll
                for (int kb = 0; kb < 6; ++kb)
#pragma unroll
                    for (int i = 0; i < 2; ++i) {
                        float a = bf_lo(a1[kb][2 * i]), b = bf_hi(a1[kb][2 * i]);
                        s0[0] += a; v0[0] = fmaf(a, a, v0[0]); s0[1] += b; v0[1] = fmaf(b, b, v0[1]);
                        a = bf_lo(a1[kb][2 * i + 1]); b = bf_hi(a1[kb][2 * i + 1]);
                        s1[0] += a; v1[0] = fmaf(a, a, v1[0]); s1[1] += b; v1[1] = fmaf(b, b, v1[1]);
                    }
                float sa = s0[0] + s0[1], sb = s1[0] + s1[1], va = v0[0] + v0[1], vb = v1[0] + v1[1];
                sa += __shfl_xor_sync(0xffffffffu, sa, 1); sb += __shfl_xor_sync(0xffffffffu, sb, 1);
                va += __shfl_xor_sync(0xffffffffu, va, 1); vb += __shfl_xor_sync(0xffffffffu, vb, 1);
                sa += __shfl_xor_sync(0xffffffffu, sa, 2); sb += __shfl_xor_sync(0xffffffffu, sb, 2);
                va += __shfl_xor_sync(0xffffffffu, va, 2); vb += __shfl_xor_sync(0xffffffffu, vb, 2);
                m0 = sa * (1.f / CH); m1 = sb * (1.f / CH);
                asm("rsqrt.approx.ftz.f32 %0, %1;" : "=f"(r0) : "f"(fmaxf(fmaf(-m0, m0, va * (1.f / CH)), 0.f) + 1e-5f));
                asm("rsqrt.approx.ftz.f32 %0, %1;" : "=f"(r1) : "f"(fmaxf(fmaf(-m1, m1, vb * (1.f / CH)), 0.f) + 1e-5f));
                r0 *= GELU_A; r1 *= GELU_A;
                const float o0 = -m0 * r0, o1 = -m1 * r1;
#pragma unroll
                for (int kb = 0; kb < 6; ++kb)
#pragma unroll
                    for (int i = 0; i < 4; ++i) {
                        const float r = (i & 1) ? r1 : r0, o = (i & 1) ? o1 : o0;
                        a1[kb][i] = pack_f16(fmaf(bf_lo(a1[kb][i]), r, o), fmaf(bf_hi(a1[kb][i]), r, o));
                    }
            }
            if (q == 3) {
                a1[5][2] = (a1[5][2] & 0xffffu) | 0x3C000000u;
                a1[5][3] = (a1[5][3] & 0xffffu) | 0x3C000000u;
            }
        };
        auto gemm1 = [&](uint32_t (&d)[NCH / 4], int c) {
            WH<NCH>::first(d, a1[0][0], a1[0][1], a1[0][2], a1[0][3], descW1 + (uint64_t)(c * 768));
#pragma unroll
            for (int kk = 1; kk < 6; ++kk)
                WH<NCH>::acc(d, a1[kk][0], a1[kk][1], a1[kk][2], a1[kk][3], descW1 + (uint64_t)(c * 768 + kk * 128));
        };
        auto init_acc = [&]() {
#pragma unroll
            for (int m = 0; m < 6; ++m) {
                const uint4 v = lds128(sbase + OFF_B2I + m * 64 + q * 16);
                acc2[4 * m] = v.x; acc2[4 * m + 1] = v.y; acc2[4 * m + 2] = v.z; acc2[4 * m + 3] = v.w;
            }
        };

        mbar_wait(bars + 8 * (BAR_DONE + wg), 0);
        load_a();
        TL(104);
        partial_a();
        wg_fence();
        reduce_a();
        wg_commit();
        wg_wait<0>();
        fence_regs(st);
        norm_a();
        TL(105);
        __syncwarp();
        if (elect_one()) mbar_arrive(bars + 8 * (BAR_A_EMPTY + (wg & 1)));
        wg_fence();
        gemm1(h[0], 0);
        wg_commit();
        wg_wait<0>();
        uint32_t y[24];
#pragma unroll
        for (int i = 0; i < 24; ++i) y[i] = 0;
        auto flush_y = [&](__nv_bfloat16* p) {
#pragma unroll
            for (int jj = 0; jj < 3; ++jj)
#pragma unroll
                for (int hrow = 0; hrow < 2; ++hrow)
                    red_add_bf16x8(p + hrow * 8 * CH + jj * 32, y[jj * 8 + hrow], y[jj * 8 + hrow + 2], y[jj * 8 + hrow + 4], y[jj * 8 + hrow + 6]);
        };
        __nv_bfloat16* optr = out + ((ys + dir * (wg + 1 - NMLP)) * IMG_W + strip * STRIP_W + wr * 16 + g) * CH + q * 8;
#pragma unroll 1
        for (int t = wg; t < ROWS_PER_CTA; t += NMLP) {
            TL(4 + 2 * (t / NMLP));
            const bool more = t + NMLP < ROWS_PER_CTA;
            const uint32_t nbar = bars + 8 * (BAR_DONE + ((t + NMLP) & 3)), nph = ((t + NMLP) >> 2) & 1;
            bool ready = true;
            SCHED_FENCE();
            init_acc();
#pragma unroll
            for (int c = 0; c < NCHUNK; ++c) {
                if (c > 0) wg_wait<1>();
                fence_regs(h[c & 1]);
                if (c + 1 == NCHUNK) {
                    load_a();
                    SCHED_FENCE();
                }
                if (c + 2 == NCHUNK) ready = mbar_test(nbar, nph) || !more;
                if (c == 2) {
                    static_assert(NMLP & 1, "slot alternates");
                    asm volatile("add.u32 %0, %0, %1;" : "+r"(la) : "r"((t & 1) ? -A_BYTES : A_BYTES));
                    asm volatile("add.u64 %0, %0, %1;" : "+l"(optr) : "l"((long long)dir * (NMLP * IMG_W * CH * 2)));
                }
#pragma unroll
                for (int j = 0; j < SPLIT; ++j) h[c & 1][j] = gelu2x(h[c & 1][j]);
                if (c + 1 < NCHUNK) {
                    fence_regs(h[c & 1]);
                    if (c > 0) wg_wait<0>();
                    wg_fence();
                    gemm1(h[(c + 1) & 1], c + 1);
                    wg_commit();
                }
#pragma unroll
                for (int j = SPLIT; j < NCH / 4; ++j) {
                    if (j == (c + 1 == NCHUNK ? PSPLIT : FSPLIT)) { fence_regs(h[c & 1]); SCHED_FENCE(); }
                    h[c & 1][j] = gelu2x(h[c & 1][j]);
                }
                if (c + 1 == NCHUNK) partial_a();
                wg_fence();
                if (c + 1 == NCHUNK) {
                    reduce_a();
                    wg_commit();
                }
#pragma unroll
                for (int kk = 0; kk < NCH / 16; ++kk)
                    WH<96>::acc(acc2, h[c & 1][kk * 4], h[c & 1][kk * 4 + 1], h[c & 1][kk * 4 + 2], h[c & 1][kk * 4 + 3],
                                descW2 + (uint64_t)(((c * (NCH / 8) + 2 * kk) * (CH / 8)) * 8));
                wg_commit();
                if (c == 0 && t != wg) flush_y(optr);
                if (c + 2 == NCHUNK && !ready) mbar_wait(nbar, nph);
            }
            if (more && elect_one()) mbar_arrive(bars + 8 * (BAR_A_EMPTY + ((t + NMLP) & 1)));
            wg_wait<1>();
            fence_regs(st);
            norm_a();
            wg_wait<0>();
            fence_regs(acc2);
            wg_fence();
            gemm1(h[0], 0);
            wg_commit();
            TL(5 + 2 * (t / NMLP));
#pragma unroll
            for (int i = 0; i < 24; ++i) y[i] = h2_to_bf2(acc2[i]);
            if (oscale != 0x3F803F80u) {
#pragma unroll
                for (int i = 0; i < 24; ++i) y[i] = hmul2_bf16(y[i], oscale);
            }
            wg_wait<0>();
        }
        flush_y(optr);
        CK_END();
    }
}

typedef CUresult (*PFN_encodeTiled)(CUtensorMap*, CUtensorMapDataType, cuuint32_t, void*, const cuuint64_t*,
                                    const cuuint64_t*, const cuuint32_t*, const cuuint32_t*, CUtensorMapInterleave,
                                    CUtensorMapSwizzle, CUtensorMapL2promotion, CUtensorMapFloatOOBfill);

}

extern "C" void kernel_launch(void* const* d_in, const int* in_sizes, int n_in, void* d_out, int out_size) {
    const __nv_bfloat16* x = (const __nv_bfloat16*)d_in[0];
    const __nv_bfloat16* dw = (const __nv_bfloat16*)d_in[1];
    const __nv_bfloat16* w1 = (const __nv_bfloat16*)d_in[2];
    const __nv_bfloat16* b1 = (const __nv_bfloat16*)d_in[3];
    const __nv_bfloat16* w2 = (const __nv_bfloat16*)d_in[4];
    const __nv_bfloat16* b2 = (const __nv_bfloat16*)d_in[5];
    const __nv_bfloat16* gamma = (const __nv_bfloat16*)d_in[6];
    __nv_bfloat16* out = (__nv_bfloat16*)d_out;

    static PFN_encodeTiled encode = nullptr;
    if (!encode) {
        void* fn = nullptr;
        cudaDriverEntryPointQueryResult qres;
        cudaGetDriverEntryPoint("cuTensorMapEncodeTiled", &fn, cudaEnableDefault, &qres);
        encode = (PFN_encodeTiled)fn;
        cudaFuncSetAttribute(convnext_fused_kernel, cudaFuncAttributeMaxDynamicSharedMemorySize, SMEM_BYTES);
    }
    CUtensorMap xmap, w1map;
    cuuint64_t gdim[3] = {CH, IMG_W, IMG_H};
    cuuint64_t gstr[2] = {CH * 2, (cuuint64_t)IMG_W * CH * 2};
    cuuint32_t box[3] = {CH, HALF_W, 1};
    cuuint32_t estr[3] = {1, 1, 1};
    encode(&xmap, CU_TENSOR_MAP_DATA_TYPE_BFLOAT16, 3, (void*)x, gdim, gstr, box, estr, CU_TENSOR_MAP_INTERLEAVE_NONE,
           CU_TENSOR_MAP_SWIZZLE_NONE, CU_TENSOR_MAP_L2_PROMOTION_L2_256B, CU_TENSOR_MAP_FLOAT_OOB_FILL_NONE);
    cuuint64_t wdim[2] = {HID, CH};
    cuuint64_t wstr[1] = {HID * 2};
    cuuint32_t wbox[2] = {NCH, CH};
    encode(&w1map, CU_TENSOR_MAP_DATA_TYPE_BFLOAT16, 2, (void*)w1, wdim, wstr, wbox, estr, CU_TENSOR_MAP_INTERLEAVE_NONE,
           CU_TENSOR_MAP_SWIZZLE_128B, CU_TENSOR_MAP_L2_PROMOTION_L2_256B, CU_TENSOR_MAP_FLOAT_OOB_FILL_NONE);

    convnext_fused_kernel<<<NUM_CTAS, NUM_THREADS, SMEM_BYTES>>>(xmap, w1map, dw, w1, b1, w2, b2, gamma, out, 0u);
}
```

```cpp
#include <cuda_runtime.h>
#include <cuda_bf16.h>
#include <cuda.h>
#include <stdint.h>

namespace {

constexpr int IMG_H = 512, IMG_W = 512, CH = 96, HID = 384;
constexpr int STRIP_W = 64;
constexpr int NUM_STRIPS = IMG_W / STRIP_W;
constexpr int ROWS_PER_CTA = 32;
constexpr int NUM_CTAS = NUM_STRIPS * (IMG_H / ROWS_PER_CTA);
constexpr int HALF_W = STRIP_W / 2 + 3;
constexpr int HALF_BYTES = HALF_W * CH * 2;
constexpr int HALF_BOX = ((HALF_BYTES + 127) / 128) * 128;
constexpr int HALF_OFF = HALF_BOX + CH * 2;
constexpr int ROW_BYTES = 2 * HALF_BOX;
constexpr int NROW = 4;
#define RMLP 128
#define RCONV (512 - 3 * RMLP)
#define LAG 3
#define LB LAG
#define STG 3
#define G1POS 10
#define STATPOS 94
#define UNC 1
#define REDPOS 8
#define REDSTEP 6
#define INITPOS 6
#define TESTPOS 4
#define XPROMO CU_TENSOR_MAP_L2_PROMOTION_L2_128B
#define TOKPOS 100
#define WMASK 0xffffffffu
#define EARLYREF 1
#define ORDER "Ad012b3"
#define NROW0 1
#define NROW1 3
#define PF0 0
constexpr int NA = 2;
constexpr int A_PITCH = CH * 2 + 16;
constexpr int A_HALF = 32 * A_PITCH + 64;
constexpr int A_BYTES = ((A_HALF + 32 * A_PITCH + 127) / 128) * 128;
constexpr int NCH = 64;
constexpr int NCHUNK = HID / NCH;
#define SPLIT_ 2
#define PSPLIT 11
#define FSPLIT 10
constexpr int SPLIT = SPLIT_;
constexpr int NMLP = 3;

constexpr int OFF_W1 = 0;
constexpr int OFF_W2 = OFF_W1 + CH * HID * 2;
constexpr int OFF_ROW = OFF_W2 + CH * HID * 2;
constexpr int OFF_A = OFF_ROW + NROW * ROW_BYTES;
constexpr int OFF_ONES = OFF_A + NA * A_BYTES;
constexpr int OFF_B2I = OFF_ONES + 512;
constexpr int OFF_MAX = OFF_B2I + 384;
constexpr int OFF_DW = OFF_MAX + 128;
constexpr int OFF_BAR = OFF_DW + 9 * CH * 2;
constexpr int BAR_ROW_FULL = 0, BAR_DONE = NROW, BAR_PRIME = BAR_DONE + 4, BAR_FREE = BAR_PRIME + 1, BAR_A_EMPTY = BAR_FREE + 2;
constexpr int BAR_W1 = BAR_A_EMPTY + NA, BAR_W2 = BAR_W1 + NCHUNK, BAR_DW = BAR_W2 + NCHUNK;
constexpr int NUM_BARS = BAR_DW + 1;
constexpr int SMEM_BYTES = OFF_BAR + NUM_BARS * 8;
static_assert(SMEM_BYTES <= 232448, "smem");
static_assert(HALF_OFF % 128 == 64 && OFF_ROW % 128 == 0 && OFF_ONES % 128 == 0, "bank layout");

constexpr int NUM_THREADS = 128 * (NMLP + 1);

constexpr float GELU_A = 0.7978845608028654f / 2.423828125f;
constexpr float GELU_INV2A = 0.5f / GELU_A;

__device__ __forceinline__ uint32_t smem_u32(const void* p) { return (uint32_t)__cvta_generic_to_shared(p); }

__device__ __forceinline__ void mbar_init(uint32_t bar, uint32_t count) {
    asm volatile("mbarrier.init.shared::cta.b64 [%0], %1;" ::"r"(bar), "r"(count) : "memory");
}
__device__ __forceinline__ void mbar_expect_tx(uint32_t bar, uint32_t bytes) {
    asm volatile("mbarrier.arrive.expect_tx.shared::cta.b64 _, [%0], %1;" ::"r"(bar), "r"(bytes) : "memory");
}
__device__ __forceinline__ void mbar_arrive(uint32_t bar) {
    asm volatile("mbarrier.arrive.shared::cta.b64 _, [%0];" ::"r"(bar) : "memory");
}
__device__ __forceinline__ bool mbar_try(uint32_t bar, uint32_t parity) {
    uint32_t done;
    asm volatile(
        "{\n\t.reg .pred p;\n\t"
        "mbarrier.try_wait.parity.shared::cta.b64 p, [%1], %2;\n\t"
        "selp.u32 %0, 1, 0, p;\n\t}"
        : "=r"(done) : "r"(bar), "r"(parity) : "memory");
    return done != 0;
}
__device__ __forceinline__ bool mbar_test(uint32_t bar, uint32_t parity) {
    uint32_t done;
    asm volatile(
        "{\n\t.reg .pred p;\n\t"
        "mbarrier.test_wait.parity.shared::cta.b64 p, [%1], %2;\n\t"
        "selp.u32 %0, 1, 0, p;\n\t}"
        : "=r"(done) : "r"(bar), "r"(parity) : "memory");
    return done != 0;
}
__device__ __forceinline__ void mbar_wait(uint32_t bar, uint32_t parity) {
    for (int it = 0; it < (1 << 20); ++it)
        if (mbar_try(bar, parity)) break;
}
__device__ __forceinline__ uint64_t policy_evict_first() {
    uint64_t p;
    asm("createpolicy.fractional.L2::evict_first.b64 %0, 1.0;" : "=l"(p));
    return p;
}
__device__ __forceinline__ void tma_load_3d(uint32_t dst, const CUtensorMap* map, uint32_t bar, int c0, int c1, int c2) {
    asm volatile(
        "cp.async.bulk.tensor.3d.shared::cluster.global.mbarrier::complete_tx::bytes.L2::cache_hint [%0], [%1, {%3, %4, %5}], [%2], %6;"
        ::"r"(dst), "l"(reinterpret_cast<uint64_t>(map)), "r"(bar), "r"(c0), "r"(c1), "r"(c2), "l"(policy_evict_first()) : "memory");
}
__device__ __forceinline__ void tma_load_2d(uint32_t dst, const CUtensorMap* map, uint32_t bar, int c0, int c1) {
    asm volatile(
        "cp.async.bulk.tensor.2d.shared::cluster.global.mbarrier::complete_tx::bytes [%0], [%1, {%3, %4}], [%2];"
        ::"r"(dst), "l"(reinterpret_cast<uint64_t>(map)), "r"(bar), "r"(c0), "r"(c1) : "memory");
}
__device__ __forceinline__ bool elect_one() {
    uint32_t p;
    asm volatile("{\n\t.reg .pred p;\n\telect.sync _|p, 0xffffffff;\n\tselp.u32 %0, 1, 0, p;\n\t}" : "=r"(p));
    return p != 0;
}
__device__ __forceinline__ void bulk_load(uint32_t dst, const void* src, uint32_t bytes, uint32_t bar) {
    asm volatile("cp.async.bulk.shared::cluster.global.mbarrier::complete_tx::bytes [%0], [%1], %2, [%3];"
                 ::"r"(dst), "l"(src), "r"(bytes), "r"(bar) : "memory");
}
__device__ __forceinline__ void bulk_store(void* dst, uint32_t src, uint32_t bytes) {
    asm volatile("cp.async.bulk.global.shared::cta.bulk_group [%0], [%1], %2;" ::"l"(dst), "r"(src), "r"(bytes) : "memory");
}
__device__ __forceinline__ void bulk_commit() { asm volatile("cp.async.bulk.commit_group;" ::: "memory"); }
template <int N> __device__ __forceinline__ void bulk_wait_read() {
    asm volatile("cp.async.bulk.wait_group.read %0;" ::"n"(N) : "memory");
}
template <int N> __device__ __forceinline__ void bulk_wait() {
    asm volatile("cp.async.bulk.wait_group %0;" ::"n"(N) : "memory");
}
__device__ __forceinline__ void ldsm_x4(uint32_t addr, uint32_t& r0, uint32_t& r1, uint32_t& r2, uint32_t& r3) {
    asm volatile("ldmatrix.sync.aligned.m8n8.x4.shared.b16 {%0,%1,%2,%3}, [%4];"
                 : "=r"(r0), "=r"(r1), "=r"(r2), "=r"(r3) : "r"(addr) : "memory");
}
__device__ __forceinline__ void ldsm_x2(uint32_t addr, uint32_t& r0, uint32_t& r1) {
    asm volatile("ldmatrix.sync.aligned.m8n8.x2.shared.b16 {%0,%1}, [%2];" : "=r"(r0), "=r"(r1) : "r"(addr) : "memory");
}
__device__ __forceinline__ void stsm_x4(uint32_t addr, uint32_t r0, uint32_t r1, uint32_t r2, uint32_t r3) {
    asm volatile("stmatrix.sync.aligned.m8n8.x4.shared.b16 [%0], {%1,%2,%3,%4};"
                 ::"r"(addr), "r"(r0), "r"(r1), "r"(r2), "r"(r3) : "memory");
}
__device__ __forceinline__ uint4 lds128(uint32_t addr) {
    uint4 v;
    asm volatile("ld.shared.v4.u32 {%0,%1,%2,%3}, [%4];" : "=r"(v.x), "=r"(v.y), "=r"(v.z), "=r"(v.w) : "r"(addr) : "memory");
    return v;
}
__device__ __forceinline__ uint32_t lds32(uint32_t addr) {
    uint32_t a;
    asm volatile("ld.shared.u32 %0, [%1];" : "=r"(a) : "r"(addr) : "memory");
    return a;
}
__device__ __forceinline__ void sts32(uint32_t addr, uint32_t a) {
    asm volatile("st.shared.u32 [%0], %1;" ::"r"(addr), "r"(a) : "memory");
}
__device__ __forceinline__ void sts128(uint32_t addr, uint32_t a, uint32_t b, uint32_t c, uint32_t d) {
    asm volatile("st.shared.v4.u32 [%0], {%1,%2,%3,%4};" ::"r"(addr), "r"(a), "r"(b), "r"(c), "r"(d) : "memory");
}
__device__ __forceinline__ uint32_t hfma2_bf16(uint32_t a, uint32_t b, uint32_t c) {
    uint32_t d;
    asm("fma.rn.bf16x2 %0, %1, %2, %3;" : "=r"(d) : "r"(a), "r"(b), "r"(c));
    return d;
}
__device__ __forceinline__ uint32_t hmul2_bf16(uint32_t a, uint32_t b) {
    uint32_t d;
    asm("mul.rn.bf16x2 %0, %1, %2;" : "=r"(d) : "r"(a), "r"(b));
    return d;
}
__device__ __forceinline__ uint32_t hadd2_bf16(uint32_t a, uint32_t b) {
    uint32_t d;
    asm("add.rn.bf16x2 %0, %1, %2;" : "=r"(d) : "r"(a), "r"(b));
    return d;
}
__device__ __forceinline__ float bf_lo(uint32_t v) { return __uint_as_float(v << 16); }
__device__ __forceinline__ float bf_hi(uint32_t v) { return __uint_as_float(v & 0xffff0000u); }
__device__ __forceinline__ uint32_t pack_bf16(float lo, float hi) {
    uint32_t d;
    asm("cvt.rn.bf16x2.f32 %0, %1, %2;" : "=r"(d) : "f"(hi), "f"(lo));
    return d;
}
__device__ __forceinline__ uint32_t pack_f16(float lo, float hi) {
    uint32_t d;
    asm("cvt.rn.f16x2.f32 %0, %1, %2;" : "=r"(d) : "f"(hi), "f"(lo));
    return d;
}
__device__ __forceinline__ uint32_t scale2h(uint32_t v, float s) {
    return pack_f16(bf_lo(v) * s, bf_hi(v) * s);
}
__device__ __forceinline__ uint32_t h2_to_bf2(uint32_t v) {
    uint32_t d;
    asm("{\n\t.reg .b16 l, h;\n\t.reg .f32 a, b;\n\tmov.b32 {l, h}, %1;\n\tcvt.f32.f16 a, l;\n\tcvt.f32.f16 b, h;\n\t"
        "cvt.rn.bf16x2.f32 %0, b, a;\n\t}" : "=r"(d) : "r"(v));
    return d;
}
__device__ __forceinline__ uint32_t hsub2_f16(uint32_t a, uint32_t b) {
    uint32_t d;
    asm("sub.rn.f16x2 %0, %1, %2;" : "=r"(d) : "r"(a), "r"(b));
    return d;
}
__device__ __forceinline__ uint32_t hmul2_f16(uint32_t a, uint32_t b) {
    uint32_t d;
    asm("mul.rn.f16x2 %0, %1, %2;" : "=r"(d) : "r"(a), "r"(b));
    return d;
}
__device__ __forceinline__ uint32_t bf2_to_h2(uint32_t y) { return (y & 0x7fff7fffu) * 7u + y; }
__device__ __forceinline__ uint32_t absmax2(uint32_t m, uint32_t v) { return __vmaxu2(m, v & 0x7fff7fffu); }
__device__ __forceinline__ void red_add_bf16x8(void* p, uint32_t a, uint32_t b, uint32_t c, uint32_t d) {
    asm volatile("red.global.add.noftz.v4.bf16x2 [%0], {%1,%2,%3,%4};" ::"l"(p), "r"(a), "r"(b), "r"(c), "r"(d) : "memory");
}
__device__ __forceinline__ void red_add_bf16x8_if(bool pr, void* p, uint32_t a, uint32_t b, uint32_t c, uint32_t d) {
    asm volatile("{\n\t.reg .pred p;\n\tsetp.ne.u32 p, %5, 0;\n\t@p red.global.add.noftz.v4.bf16x2 [%0], {%1,%2,%3,%4};\n\t}"
                 ::"l"(p), "r"(a), "r"(b), "r"(c), "r"(d), "r"((uint32_t)pr) : "memory");
}
__device__ __forceinline__ uint32_t gelu2x(uint32_t v) {
    uint32_t p, z, t, g;
    asm("fma.rn.f16x2 %0, %1, %1, %2;" : "=r"(p) : "r"(v), "r"(0x40D940D9u));
    asm("mul.rn.f16x2 %0, %1, %2;" : "=r"(z) : "r"(v), "r"(p));
    asm("tanh.approx.f16x2 %0, %1;" : "=r"(t) : "r"(z));
    asm("fma.rn.f16x2 %0, %1, %2, %1;" : "=r"(g) : "r"(v), "r"(t));
    return g;
}
__device__ __forceinline__ void wg_fence() { asm volatile("wgmma.fence.sync.aligned;" ::: "memory"); }
__device__ __forceinline__ void wg_commit() { asm volatile("wgmma.commit_group.sync.aligned;" ::: "memory"); }
template <int N> __device__ __forceinline__ void wg_wait() {
    asm volatile("wgmma.wait_group.sync.aligned %0;" ::"n"(N) : "memory");
}
template <int N> __device__ __forceinline__ void fence_regs(float (&d)[N]) {
#pragma unroll
    for (int i = 0; i < N; ++i) asm volatile("" : "+f"(d[i])::"memory");
}
template <int N> __device__ __forceinline__ void fence_regs(uint32_t (&d)[N]) {
#pragma unroll
    for (int i = 0; i < N; ++i) asm volatile("" : "+r"(d[i])::"memory");
}

template <int N> struct WH;
template <> struct WH<64> {
    static __device__ __forceinline__ void acc(uint32_t* d, uint32_t a0, uint32_t a1, uint32_t a2, uint32_t a3, uint64_t desc) {
        asm volatile("wgmma.mma_async.sync.aligned.m64n64k16.f16.f16.f16 {%0,%1,%2,%3,%4,%5,%6,%7,%8,%9,%10,%11,%12,%13,%14,%15}, "
                     "{%16,%17,%18,%19}, %20, 1, 1, 1, 1;"
                     : "+r"(d[0]), "+r"(d[1]), "+r"(d[2]), "+r"(d[3]), "+r"(d[4]), "+r"(d[5]), "+r"(d[6]), "+r"(d[7]), "+r"(d[8]), "+r"(d[9]), "+r"(d[10]), "+r"(d[11]), "+r"(d[12]), "+r"(d[13]), "+r"(d[14]), "+r"(d[15])
                     : "r"(a0), "r"(a1), "r"(a2), "r"(a3), "l"(desc) : "memory");
    }
    static __device__ __forceinline__ void first(uint32_t* d, uint32_t a0, uint32_t a1, uint32_t a2, uint32_t a3, uint64_t desc) {
        asm volatile("wgmma.mma_async.sync.aligned.m64n64k16.f16.f16.f16 {%0,%1,%2,%3,%4,%5,%6,%7,%8,%9,%10,%11,%12,%13,%14,%15}, "
                     "{%16,%17,%18,%19}, %20, 0, 1, 1, 1;"
                     : "=r"(d[0]), "=r"(d[1]), "=r"(d[2]), "=r"(d[3]), "=r"(d[4]), "=r"(d[5]), "=r"(d[6]), "=r"(d[7]), "=r"(d[8]), "=r"(d[9]), "=r"(d[10]), "=r"(d[11]), "=r"(d[12]), "=r"(d[13]), "=r"(d[14]), "=r"(d[15])
                     : "r"(a0), "r"(a1), "r"(a2), "r"(a3), "l"(desc) : "memory");
    }
};
template <> struct WH<96> {
    static __device__ __forceinline__ void acc(uint32_t* d, uint32_t a0, uint32_t a1, uint32_t a2, uint32_t a3, uint64_t desc) {
        asm volatile("wgmma.mma_async.sync.aligned.m64n96k16.f16.f16.f16 {%0,%1,%2,%3,%4,%5,%6,%7,%8,%9,%10,%11,%12,%13,%14,%15,%16,%17,%18,%19,%20,%21,%22,%23}, "
                     "{%24,%25,%26,%27}, %28, 1, 1, 1, 1;"
                     : "+r"(d[0]), "+r"(d[1]), "+r"(d[2]), "+r"(d[3]), "+r"(d[4]), "+r"(d[5]), "+r"(d[6]), "+r"(d[7]), "+r"(d[8]), "+r"(d[9]), "+r"(d[10]), "+r"(d[11]), "+r"(d[12]), "+r"(d[13]), "+r"(d[14]), "+r"(d[15]), "+r"(d[16]), "+r"(d[17]), "+r"(d[18]), "+r"(d[19]), "+r"(d[20]), "+r"(d[21]), "+r"(d[22]), "+r"(d[23])
                     : "r"(a0), "r"(a1), "r"(a2), "r"(a3), "l"(desc) : "memory");
    }
    static __device__ __forceinline__ void first(uint32_t* d, uint32_t a0, uint32_t a1, uint32_t a2, uint32_t a3, uint64_t desc) {
        asm volatile("wgmma.mma_async.sync.aligned.m64n96k16.f16.f16.f16 {%0,%1,%2,%3,%4,%5,%6,%7,%8,%9,%10,%11,%12,%13,%14,%15,%16,%17,%18,%19,%20,%21,%22,%23}, "
                     "{%24,%25,%26,%27}, %28, 0, 1, 1, 1;"
                     : "=r"(d[0]), "=r"(d[1]), "=r"(d[2]), "=r"(d[3]), "=r"(d[4]), "=r"(d[5]), "=r"(d[6]), "=r"(d[7]), "=r"(d[8]), "=r"(d[9]), "=r"(d[10]), "=r"(d[11]), "=r"(d[12]), "=r"(d[13]), "=r"(d[14]), "=r"(d[15]), "=r"(d[16]), "=r"(d[17]), "=r"(d[18]), "=r"(d[19]), "=r"(d[20]), "=r"(d[21]), "=r"(d[22]), "=r"(d[23])
                     : "r"(a0), "r"(a1), "r"(a2), "r"(a3), "l"(desc) : "memory");
    }
};

__device__ __forceinline__ void wgmma_stat_first(float (&d)[4], const uint32_t (&a)[4], uint64_t desc) {
    asm volatile("wgmma.mma_async.sync.aligned.m64n8k16.f32.bf16.bf16 {%0,%1,%2,%3}, {%4,%5,%6,%7}, %8, 0, 1, 1, 1;"
                 : "=f"(d[0]), "=f"(d[1]), "=f"(d[2]), "=f"(d[3]) : "r"(a[0]), "r"(a[1]), "r"(a[2]), "r"(a[3]), "l"(desc) : "memory");
}
__device__ __forceinline__ void wgmma_stat_acc(float (&d)[4], const uint32_t (&a)[4], uint64_t desc) {
    asm volatile("wgmma.mma_async.sync.aligned.m64n8k16.f32.bf16.bf16 {%0,%1,%2,%3}, {%4,%5,%6,%7}, %8, 1, 1, 1, 1;"
                 : "+f"(d[0]), "+f"(d[1]), "+f"(d[2]), "+f"(d[3]) : "r"(a[0]), "r"(a[1]), "r"(a[2]), "r"(a[3]), "l"(desc) : "memory");
}

__device__ __forceinline__ uint64_t make_desc(uint32_t addr, uint32_t lbo, uint32_t sbo) {
    return (uint64_t)((addr & 0x3FFFF) >> 4) | ((uint64_t)(lbo >> 4) << 16) | ((uint64_t)(sbo >> 4) << 32);
}

#define CK_BEGIN()
#define CK_END()
#define TL(slot)

#define SCHED_FENCE() asm volatile("{\n\t.reg .pred p;\n\tsetp.ne.u32 p, %0, 0;\n\t@p exit;\n\t}" ::"r"(zero) : "memory")

__global__ void __launch_bounds__(NUM_THREADS, 1)
convnext_fused_kernel(const __grid_constant__ CUtensorMap xmap, const __grid_constant__ CUtensorMap w1map,
                      const __nv_bfloat16* __restrict__ dw, const __nv_bfloat16* __restrict__ w1,
                      const __nv_bfloat16* __restrict__ b1, const __nv_bfloat16* __restrict__ w2,
                      const __nv_bfloat16* __restrict__ b2, const __nv_bfloat16* __restrict__ gamma,
                      __nv_bfloat16* __restrict__ out, uint32_t zero) {
    extern __shared__ __align__(1024) uint8_t smem[];
    const uint32_t sbase = smem_u32(smem);
    const int tid = threadIdx.x;
    const int warp = __shfl_sync(0xffffffffu, tid >> 5, 0);
    const int lane = tid & 31;
    const int wg = warp >> 2, wr = warp & 3;
    const uint32_t bars = sbase + OFF_BAR;
    const int strip = blockIdx.x % NUM_STRIPS;
    const int band = blockIdx.x / NUM_STRIPS;
    const int dir = (band & 1) ? 1 : -1;
    const int ys = (band & 1) ? band * ROWS_PER_CTA - 1 : (band + 1) * ROWS_PER_CTA;
    TL(0);
    CK_BEGIN();

    auto load_row = [&](int j) {
        const uint32_t bar = bars + 8 * (BAR_ROW_FULL + (j & 3));
        const uint32_t dst = sbase + OFF_ROW + (j & 3) * ROW_BYTES;
        mbar_expect_tx(bar, 2 * HALF_BYTES);
        tma_load_3d(dst, &xmap, bar, 0, strip * STRIP_W - 1, ys + dir * j);
        tma_load_3d(dst + HALF_BOX, &xmap, bar, 0, strip * STRIP_W + 30, ys + dir * j);
    };
    if (warp == 11) {
        if (elect_one()) {
            for (int s = 0; s < NUM_BARS; ++s) mbar_init(bars + 8 * s, (s >= BAR_DONE && s < BAR_W1) ? (TOKPOS >= 0 && s < BAR_PRIME ? 8 : 4) : 1);
            if (TOKPOS >= 0) asm volatile("mbarrier.arrive.shared::cta.b64 _, [%0], 4;" ::"r"(bars + 8 * BAR_DONE) : "memory");
            asm volatile("fence.mbarrier_init.release.cluster;" ::: "memory");
        }
        __syncwarp();
        asm volatile("bar.arrive 2, %0;" ::"n"(NUM_THREADS) : "memory");
        if (elect_one()) {
            constexpr char order[] = ORDER;
#pragma unroll
            for (int i = 0; i < 7; ++i) {
                if (order[i] == 'A') {
#pragma unroll 1
                    for (int s = 0; s < NCHUNK; ++s) {
                        mbar_expect_tx(bars + 8 * (BAR_W1 + s), CH * NCH * 2);
                        tma_load_2d(sbase + OFF_W1 + s * (CH * NCH * 2), &w1map, bars + 8 * (BAR_W1 + s), s * NCH, 0);
                    }
                } else if (order[i] == 'b') {
#pragma unroll 1
                    for (int s = 0; s < NCHUNK; ++s) {
                        mbar_expect_tx(bars + 8 * (BAR_W2 + s), CH * NCH * 2);
                        bulk_load(sbase + OFF_W2 + s * (CH * NCH * 2), w2 + s * (CH * NCH), CH * NCH * 2, bars + 8 * (BAR_W2 + s));
                    }
                } else if (order[i] == 'd') {
                    mbar_expect_tx(bars + 8 * BAR_DW, 9 * CH * 2);
                    bulk_load(sbase + OFF_DW, dw, 9 * CH * 2, bars + 8 * BAR_DW);
                } else {
                    load_row(order[i] - '0');
                }
            }
        }
        __syncwarp();
    } else if (warp == 10) {
        if (elect_one()) asm volatile("prefetch.tensormap [%0];" ::"l"(reinterpret_cast<uint64_t>(&xmap)) : "memory");
    }
    TL(80);

    if (wg == NMLP) {
        asm volatile("setmaxnreg.dec.sync.aligned.u32 %0;" ::"n"(RCONV));
        asm volatile("bar.sync 2, %0;" ::"n"(NUM_THREADS) : "memory");
        uint32_t w[3][3][3];
        {
            mbar_wait(bars + 8 * BAR_DW, 0);
            const uint32_t wp = sbase + OFF_DW + 48 * ((wr + (lane >> 2)) & 3) + 4 * (lane & 3) + 3 * (CH * 2);
#pragma unroll
            for (int s = 0; s < 3; ++s)
#pragma unroll
                for (int t = 0; t < 9; ++t) w[t / 3][t % 3][s] = lds32(wp + (t / 3 - 1) * dir * 3 * (CH * 2) + (t % 3) * (CH * 2) + s * 16);
        }
        const int ga = lane & 7, ja = lane >> 3;
        const uint32_t ip = sbase + OFF_ROW + (uint32_t)((ga >> 2) * HALF_OFF + (8 * (ga & 3) + ja) * (CH * 2) + 48 * ((wr + ga) & 3));
        const uint32_t op = sbase + OFF_A + (uint32_t)((ga >> 2) * A_HALF + (8 * (ga & 3) + ja) * A_PITCH + 48 * ((wr + ga) & 3));
        static_assert(NROW == 4 && NA == 2, "ring arithmetic");
        uint32_t P[2][3][8], f[10], c[8];
        auto feed = [&](int e, int s, int i) {
#pragma unroll
            for (int o = i - 2; o <= i; ++o) {
                if (o < 0 || o > 7) continue;
                const int jx = i - o;
                if (jx == 0) {
                    asm volatile("fma.rn.bf16x2 %0, %3, %4, %1;\n\tfma.rn.bf16x2 %2, %3, %5, %2;\n\tmul.rn.bf16x2 %1, %3, %6;"
                                 : "=&r"(c[o]), "+r"(P[e][s][o]), "+r"(P[e ^ 1][s][o])
                                 : "r"(f[i]), "r"(w[2][0][s]), "r"(w[1][0][s]), "r"(w[0][0][s]));
                } else {
                    asm volatile("fma.rn.bf16x2 %0, %3, %4, %0;\n\tfma.rn.bf16x2 %2, %3, %5, %2;\n\tfma.rn.bf16x2 %1, %3, %6, %1;"
                                 : "+r"(c[o]), "+r"(P[e][s][o]), "+r"(P[e ^ 1][s][o])
                                 : "r"(f[i]), "r"(w[2][jx][s]), "r"(w[1][jx][s]), "r"(w[0][jx][s]));
                }
            }
        };
        constexpr int NSTEPS = ROWS_PER_CTA + 2;
        __nv_bfloat16* xo = out + ((ys + dir) * IMG_W + strip * STRIP_W + wr * 16) * CH;
        const uint32_t xs = sbase + OFF_ROW + (wr >> 1) * HALF_OFF + ((wr & 1) * 16 + 1) * (CH * 2);
        mbar_wait(bars + 8 * BAR_ROW_FULL, 0);
        TL(4);
#pragma unroll
        for (int r = 0; r < 2; ++r) {
            if (r == 1) {
                mbar_wait(bars + 8 * (BAR_ROW_FULL + 1), 0);
                if (elect_one()) {
                    bulk_store(xo, xs + ROW_BYTES, 16 * CH * 2);
                    bulk_commit();
                }
            }
#pragma unroll
            for (int s = 0; s < 3; ++s) {
                ldsm_x4(ip + r * ROW_BYTES + s * 16, f[0], f[1], f[2], f[3]);
                ldsm_x4(ip + r * ROW_BYTES + s * 16 + 4 * (CH * 2), f[4], f[5], f[6], f[7]);
                ldsm_x2(ip + r * ROW_BYTES + s * 16 + 8 * (CH * 2), f[8], f[9]);
#pragma unroll
                for (int o = 0; o < 8; ++o) {
                    if (r == 1) P[0][s][o] = hfma2_bf16(f[o + 2], w[1][2][s], hfma2_bf16(f[o + 1], w[1][1][s], hfma2_bf16(f[o], w[1][0][s], P[0][s][o])));
                    P[r][s][o] = hfma2_bf16(f[o + 2], w[0][2][s], hfma2_bf16(f[o + 1], w[0][1][s], hmul2_bf16(f[o], w[0][0][s])));
                }
            }
        }
        __syncwarp();
        if (elect_one()) {
            bulk_wait_read<0>();
            mbar_arrive(bars + 8 * BAR_PRIME);
        }
        TL(5);
        if (wr < 2) {
            mbar_wait(bars + 8 * BAR_PRIME, 0);
            if (elect_one()) load_row(4 + wr);
        }
        mbar_wait(bars + 8 * (BAR_ROW_FULL + 2), 0);
        TL(6);
        ldsm_x4(ip + 2 * ROW_BYTES, f[0], f[1], f[2], f[3]);
        ldsm_x4(ip + 2 * ROW_BYTES + 4 * (CH * 2), f[4], f[5], f[6], f[7]);
        ldsm_x2(ip + 2 * ROW_BYTES + 8 * (CH * 2), f[8], f[9]);
#pragma unroll 1
        for (int m = 0; m < ROWS_PER_CTA / 4; ++m) {
            const bool last = m + 1 == ROWS_PER_CTA / 4;
#pragma unroll
            for (int u = 0; u < 4; ++u) {
                const int j = 4 * m + u + 2;
                const int rs = (u + 2) & 3, ns = (u + 3) & 3;
                TL(4 + 6 * j + 0);
                const uint32_t ebar = bars + 8 * (BAR_A_EMPTY + (u & 1)), rbar = bars + 8 * (BAR_ROW_FULL + ns);
                const uint32_t eph = ((u >> 1) & 1) ^ 1, rph = (m + (u >= 1)) & 1;
                xo += dir * IMG_W * CH;
                if (!(u == 3 && last)) {
                    if (elect_one()) bulk_store(xo, xs + rs * ROW_BYTES, 16 * CH * 2);
                }
                bulk_commit();
                bool ok = mbar_test(ebar, eph);
#pragma unroll
                for (int s = 0; s < 3; ++s) {
                    if (s == 2) ok = mbar_test(rbar, rph) || (u == 3 && last);
                    feed(u & 1, s, 0); feed(u & 1, s, 1); feed(u & 1, s, 2); feed(u & 1, s, 3);
                    if (s == 0) {
                        if (!ok) mbar_wait(ebar, eph);
                        TL(4 + 6 * j + 1);
                    }
                    const uint32_t nx = ip + (s == 2 ? ns : rs) * ROW_BYTES + ((s + 1) % 3) * 16;
                    const uint32_t ox = op + (u & 1) * A_BYTES + s * 16;
                    ldsm_x4(nx, f[0], f[1], f[2], f[3]);
                    SCHED_FENCE();
                    feed(u & 1, s, 4); feed(u & 1, s, 5);
                    stsm_x4(ox, c[0], c[1], c[2], c[3]);
                    feed(u & 1, s, 6); feed(u & 1, s, 7);
                    ldsm_x4(nx + 4 * (CH * 2), f[4], f[5], f[6], f[7]);
                    SCHED_FENCE();
                    feed(u & 1, s, 8); feed(u & 1, s, 9);
                    stsm_x4(ox + 4 * A_PITCH, c[4], c[5], c[6], c[7]);
                    ldsm_x2(nx + 8 * (CH * 2), f[8], f[9]);
                    SCHED_FENCE();
                }
                TL(4 + 6 * j + 4);
                bulk_wait<0>();
                __syncwarp();
                if (elect_one()) {
                    mbar_arrive(bars + 8 * (BAR_DONE + u));
                    if (EARLYREF) mbar_arrive(bars + 8 * (BAR_FREE + (u & 1)));
                }
                if (wr == u && !last) {
                    mbar_wait(bars + 8 * (BAR_FREE + (u & 1)), (u >> 1) & 1);
                    if (elect_one()) load_row(j + 4);
                }
                TL(4 + 6 * j + 2);
                if (!ok) {
                    mbar_wait(rbar, rph);
                    ldsm_x4(ip + ns * ROW_BYTES, f[0], f[1], f[2], f[3]);
                    ldsm_x4(ip + ns * ROW_BYTES + 4 * (CH * 2), f[4], f[5], f[6], f[7]);
                    ldsm_x2(ip + ns * ROW_BYTES + 8 * (CH * 2), f[8], f[9]);
                }
                TL(4 + 6 * j + 5);
            }
        }
    } else {
        const int g = lane >> 2, q = lane & 3;
        uint4 r95, bb, gm[3];
        uint32_t b2v = 0, g2v = 0;
        r95 = __ldg(reinterpret_cast<const uint4*>(w1 + 95 * HID + (warp >> 1) * NCH + (lane & 7) * 8));
        bb = __ldg(reinterpret_cast<const uint4*>(b1 + (warp >> 1) * NCH + (lane & 7) * 8));
#pragma unroll
        for (int jj = 0; jj < 3; ++jj) gm[jj] = __ldg(reinterpret_cast<const uint4*>(gamma + jj * 32 + q * 8));
        if (tid < CH / 2) {
            b2v = __ldg(reinterpret_cast<const uint32_t*>(b2) + tid);
            g2v = __ldg(reinterpret_cast<const uint32_t*>(gamma) + tid);
        }
        if (warp != 11) asm volatile("bar.sync 2, %0;" ::"n"(NUM_THREADS) : "memory");
        TL(82);
        asm volatile("setmaxnreg.inc.sync.aligned.u32 %0;" ::"n"(RMLP));
        uint32_t oscale;
        {
            const int box = warp >> 1, cc = lane & 7, k0 = (warp & 1) * 48 + (lane >> 3);
            constexpr uint32_t DN = 0x07800780u;
            TL(3);
            if (warp == 0) {
                sts128(sbase + OFF_ONES + lane * 16, lane < 16 ? 0x3F80u : 0x3F800000u, lane < 16 ? 0x3F80u : 0x3F800000u,
                       lane < 16 ? 0x3F80u : 0x3F800000u, lane < 16 ? 0x3F80u : 0x3F800000u);
            }
            const uint32_t m[4] = {hmul2_bf16(r95.x, DN | 0x80008000u), hmul2_bf16(r95.y, DN | 0x80008000u),
                                   hmul2_bf16(r95.z, DN | 0x80008000u), hmul2_bf16(r95.w, DN | 0x80008000u)};
            const uint32_t tb[4] = {scale2h(bb.x, GELU_A), scale2h(bb.y, GELU_A), scale2h(bb.z, GELU_A), scale2h(bb.w, GELU_A)};
            uint32_t mx = absmax2(absmax2(absmax2(absmax2(0, hmul2_bf16(bb.x, DN)), hmul2_bf16(bb.y, DN)), hmul2_bf16(bb.z, DN)), hmul2_bf16(bb.w, DN));
            uint32_t mg = 0;
#pragma unroll
            for (int jj = 0; jj < 3; ++jj) mg = absmax2(absmax2(absmax2(absmax2(mg, gm[jj].x), gm[jj].y), gm[jj].z), gm[jj].w);
            mg = __reduce_max_sync(0xffffffffu, max(mg & 0xffffu, mg >> 16));
            if (warp < 2) {
                const uint32_t mb = __reduce_max_sync(0xffffffffu, max(b2v & 0x7fffu, (b2v >> 16) & 0x7fffu));
                if (lane == 0) sts32(sbase + OFF_MAX + 48 + warp * 4, mb);
            }
            const uint32_t wb = sbase + OFF_W1 + box * (CH * NCH * 2);
            const uint32_t a0 = wb + k0 * 128 + ((cc ^ (k0 & 7)) << 4), a1_ = wb + (k0 + 4) * 128 + ((cc ^ ((k0 + 4) & 7)) << 4);
            mbar_wait(bars + 8 * (BAR_W1 + box), 0);
            TL(2);
            uint4 u[2] = {lds128(a0), lds128(a1_)};
#pragma unroll 1
            for (int i = 0; i < 6; ++i) {
                TL(90 + i);
                uint32_t t[2][4];
#pragma unroll
                for (int e = 0; e < 2; ++e) {
                    t[e][0] = hfma2_bf16(u[e].x, DN, m[0]); t[e][1] = hfma2_bf16(u[e].y, DN, m[1]);
                    t[e][2] = hfma2_bf16(u[e].z, DN, m[2]); t[e][3] = hfma2_bf16(u[e].w, DN, m[3]);
                    if (i < 5) u[e] = lds128((e ? a1_ : a0) + (i + 1) * 1024);
#pragma unroll
                    for (int x = 0; x < 4; ++x) {
                        mx = absmax2(mx, t[e][x]);
                        t[e][x] = bf2_to_h2(t[e][x]);
                    }
                }
                sts128(a0 + i * 1024, t[0][0], t[0][1], t[0][2], t[0][3]);
                sts128(a1_ + i * 1024, t[1][0], t[1][1], t[1][2], t[1][3]);
            }
            if (k0 + 44 == 95) sts128(a1_ + 5 * 1024, tb[0], tb[1], tb[2], tb[3]);
            const uint32_t m1w = __reduce_max_sync(0xffffffffu, max(mx & 0xffffu, mx >> 16));
            TL(100);
            const uint32_t w2b = sbase + OFF_W2 + warp * 4 * (8 * CH * 2);
            int s = 0;
#pragma unroll 1
            for (int pass = 0; pass < 2; ++pass) {
                const float sc = __uint_as_float((uint32_t)(127 + s) << 23) * GELU_INV2A;
                uint32_t gh[12], gl[12];
#pragma unroll
                for (int e = 0; e < 12; ++e) {
                    const uint32_t gv = (e & 3) == 0 ? gm[e / 4].x : (e & 3) == 1 ? gm[e / 4].y : (e & 3) == 2 ? gm[e / 4].z : gm[e / 4].w;
                    const float lo = bf_lo(gv) * sc * 0x1p-112f, hi = bf_hi(gv) * sc * 0x1p-112f;
                    gh[e] = pack_bf16(lo, hi);
                    gl[e] = pack_bf16(lo - bf_lo(gh[e]), hi - bf_hi(gh[e]));
                }
                mbar_wait(bars + 8 * (BAR_W2 + box), pass);
                TL(101);
                uint4 v[3];
#pragma unroll
                for (int jj = 0; jj < 3; ++jj) v[jj] = lds128(w2b + g * (CH * 2) + jj * 64 + q * 16);
                uint32_t mu = 0, ms = 0;
#pragma unroll 1
                for (int i = 0; i < 4; ++i) {
                    TL(110 + i);
                    uint32_t o[12];
#pragma unroll
                    for (int jj = 0; jj < 3; ++jj) {
                        mu = __vmaxu2(__vmaxu2(mu, v[jj].x), v[jj].y); mu = __vmaxu2(__vmaxu2(mu, v[jj].z), v[jj].w);
                        ms = __vmaxs2(__vmaxs2(ms, v[jj].x), v[jj].y); ms = __vmaxs2(__vmaxs2(ms, v[jj].z), v[jj].w);
                        o[jj * 4 + 0] = hfma2_bf16(v[jj].x, gh[jj * 4 + 0], hmul2_bf16(v[jj].x, gl[jj * 4 + 0]));
                        o[jj * 4 + 1] = hfma2_bf16(v[jj].y, gh[jj * 4 + 1], hmul2_bf16(v[jj].y, gl[jj * 4 + 1]));
                        o[jj * 4 + 2] = hfma2_bf16(v[jj].z, gh[jj * 4 + 2], hmul2_bf16(v[jj].z, gl[jj * 4 + 2]));
                        o[jj * 4 + 3] = hfma2_bf16(v[jj].w, gh[jj * 4 + 3], hmul2_bf16(v[jj].w, gl[jj * 4 + 3]));
                        if (i < 3) v[jj] = lds128(w2b + (i + 1) * (8 * CH * 2) + g * (CH * 2) + jj * 64 + q * 16);
                    }
                    __syncwarp();
#pragma unroll
                    for (int e = 0; e < 12; ++e) o[e] = bf2_to_h2(o[e]);
#pragma unroll
                    for (int jj = 0; jj < 3; ++jj)
                        stsm_x4(w2b + i * (8 * CH * 2) + jj * 512 + lane * 16, o[jj * 4], o[jj * 4 + 1], o[jj * 4 + 2], o[jj * 4 + 3]);
                }
                TL(103);
                if (tid < CH / 2) {
                    const float up = __uint_as_float((uint32_t)(127 + s) << 23);
                    const uint32_t v2 = pack_f16(bf_lo(b2v) * bf_lo(g2v) * up, bf_hi(b2v) * bf_hi(g2v) * up);
                    const uint32_t a = sbase + OFF_B2I + ((tid >> 4) * 2 + ((tid >> 1) & 1)) * 64 + ((tid >> 2) & 3) * 16 + (tid & 1) * 8;
                    sts32(a, v2); sts32(a + 4, v2);
                }
                mu = __vmaxu2(mu & 0x7fff7fffu, ms);
                mu = __reduce_max_sync(0xffffffffu, max(mu & 0xffffu, mu >> 16));
                if (lane == 0) sts32(sbase + OFF_MAX + warp * 4, mu | (m1w << 16));
                asm volatile("fence.proxy.async.shared::cta;" ::: "memory");
                asm volatile("bar.sync 1, %0;" ::"n"(NMLP * 128) : "memory");
                if (pass == 1) break;
                const uint32_t mm = lane < 14 ? lds32(sbase + OFF_MAX + lane * 4) : 0;
                const uint32_t m1 = __reduce_max_sync(0xffffffffu, mm >> 16);
                const uint32_t m2 = __reduce_max_sync(0xffffffffu, lane < 12 ? mm & 0xffffu : 0);
                const uint32_t mb = __reduce_max_sync(0xffffffffu, lane < 12 ? 0 : mm);
                const int e1 = max((int)(m1 >> 7), 1) - 14, eg = (int)(mg >> 7) - 126, ew = (int)(m2 >> 7) - 126;
                const int e2 = ew + eg + 1, eb = (int)(mb >> 7) - 126 + eg;
                s = min(min(-1 - e1 - e2, 14 - eb), 14 - e2);
                if (s >= 0 && s <= 12 && e2 >= -9 && eg >= -9) { s = 0; break; }
                s = min(max(s, -120), min(120, 120 - eg));
                if ((warp & 1) == 0 && elect_one()) {
                    mbar_expect_tx(bars + 8 * (BAR_W2 + box), CH * NCH * 2);
                    bulk_load(sbase + OFF_W2 + box * (CH * NCH * 2), w2 + box * (CH * NCH), CH * NCH * 2, bars + 8 * (BAR_W2 + box));
                }
            }
            oscale = (uint32_t)(127 - s) * 0x00800080u;
        }
        TL(1);
        const uint64_t descW1 = make_desc(sbase + OFF_W1, CH * NCH * 2, 1024) | (1ull << 62);
        const uint64_t descW2 = make_desc(sbase + OFF_W2, (CH / 8) * 128, 128);
        const uint64_t descS = make_desc(sbase + OFF_ONES, 128, 128);
        uint32_t la = sbase + OFF_A + (wg & 1) * A_BYTES + wr * 16 * A_PITCH + (wr >> 1) * 64 +
                            (uint32_t)(((lane & 7) + ((lane >> 3) & 1) * 8) * A_PITCH + (lane >> 4) * 16);

        uint32_t acc2[24];
        uint32_t h[2][NCH / 4];
        uint32_t a1[6][4];
        uint32_t ps[4], pq[4];
        float st[4];

        auto load_a = [&]() {
#pragma unroll
            for (int kb = 0; kb < 6; ++kb) ldsm_x4(la + kb * 32, a1[kb][0], a1[kb][1], a1[kb][2], a1[kb][3]);
        };
        auto partial_a = [&](int i) {
            {
                ps[i] = hadd2_bf16(hadd2_bf16(hadd2_bf16(a1[0][i], a1[1][i]), hadd2_bf16(a1[2][i], a1[3][i])), hadd2_bf16(a1[4][i], a1[5][i]));
                pq[i] = hmul2_bf16(a1[0][i], a1[0][i]);
#pragma unroll
                for (int kb = 1; kb < 6; ++kb) pq[i] = hfma2_bf16(a1[kb][i], a1[kb][i], pq[i]);
                asm volatile("" : "+r"(ps[i]), "+r"(pq[i]));
            }
        };
        auto reduce_a = [&]() {
            wgmma_stat_first(st, ps, descS);
            wgmma_stat_acc(st, pq, descS + 16);
        };
        auto norm_a = [&]() {
            float m0 = st[0] * (1.f / CH), m1 = st[2] * (1.f / CH);
            float r0, r1;
            asm("rsqrt.approx.ftz.f32 %0, %1;" : "=f"(r0) : "f"(fmaxf(fmaf(-m0, m0, st[1] * (1.f / CH)), 0.f) + 1e-5f));
            asm("rsqrt.approx.ftz.f32 %0, %1;" : "=f"(r1) : "f"(fmaxf(fmaf(-m1, m1, st[3] * (1.f / CH)), 0.f) + 1e-5f));
            const bool easy = fmaxf(fabsf(m0 * r0), fabsf(m1 * r1)) < 0.5f && fminf(r0, r1) > 0x1p-9f;
            if (__all_sync(0xffffffffu, easy)) {
                constexpr float K = GELU_A * 0x1p-112f;
                const uint32_t rp0 = pack_bf16(r0 * K, r0 * K), rp1 = pack_bf16(r1 * K, r1 * K);
                const float o0 = -m0 * bf_lo(rp0), o1 = -m1 * bf_lo(rp1);
                const uint32_t op0 = pack_bf16(o0, o0), op1 = pack_bf16(o1, o1);
#pragma unroll
                for (int kb = 0; kb < 6; ++kb)
#pragma unroll
                    for (int i = 0; i < 4; ++i) {
                        const uint32_t y = hfma2_bf16(a1[kb][i], (i & 1) ? rp1 : rp0, (i & 1) ? op1 : op0);
                        a1[kb][i] = bf2_to_h2(y);
                    }
            } else {
                float s0[2] = {0.f, 0.f}, s1[2] = {0.f, 0.f}, v0[2] = {0.f, 0.f}, v1[2] = {0.f, 0.f};
#pragma unroll
                for (int kb = 0; kb < 6; ++kb)
#pragma unroll
                    for (int i = 0; i < 2; ++i) {
                        float a = bf_lo(a1[kb][2 * i]), b = bf_hi(a1[kb][2 * i]);
                        s0[0] += a; v0[0] = fmaf(a, a, v0[0]); s0[1] += b; v0[1] = fmaf(b, b, v0[1]);
                        a = bf_lo(a1[kb][2 * i + 1]); b = bf_hi(a1[kb][2 * i + 1]);
                        s1[0] += a; v1[0] = fmaf(a, a, v1[0]); s1[1] += b; v1[1] = fmaf(b, b, v1[1]);
                    }
                float sa = s0[0] + s0[1], sb = s1[0] + s1[1], va = v0[0] + v0[1], vb = v1[0] + v1[1];
                sa += __shfl_xor_sync(0xffffffffu, sa, 1); sb += __shfl_xor_sync(0xffffffffu, sb, 1);
                va += __shfl_xor_sync(0xffffffffu, va, 1); vb += __shfl_xor_sync(0xffffffffu, vb, 1);
                sa += __shfl_xor_sync(0xffffffffu, sa, 2); sb += __shfl_xor_sync(0xffffffffu, sb, 2);
                va += __shfl_xor_sync(0xffffffffu, va, 2); vb += __shfl_xor_sync(0xffffffffu, vb, 2);
                m0 = sa * (1.f / CH); m1 = sb * (1.f / CH);
                asm("rsqrt.approx.ftz.f32 %0, %1;" : "=f"(r0) : "f"(fmaxf(fmaf(-m0, m0, va * (1.f / CH)), 0.f) + 1e-5f));
                asm("rsqrt.approx.ftz.f32 %0, %1;" : "=f"(r1) : "f"(fmaxf(fmaf(-m1, m1, vb * (1.f / CH)), 0.f) + 1e-5f));
                r0 *= GELU_A; r1 *= GELU_A;
                const float o0 = -m0 * r0, o1 = -m1 * r1;
#pragma unroll
                for (int kb = 0; kb < 6; ++kb)
#pragma unroll
                    for (int i = 0; i < 4; ++i) {
                        const float r = (i & 1) ? r1 : r0, o = (i & 1) ? o1 : o0;
                        a1[kb][i] = pack_f16(fmaf(bf_lo(a1[kb][i]), r, o), fmaf(bf_hi(a1[kb][i]), r, o));
                    }
            }
            if (q == 3) {
                a1[5][2] = (a1[5][2] & 0xffffu) | 0x3C000000u;
                a1[5][3] = (a1[5][3] & 0xffffu) | 0x3C000000u;
            }
        };
        auto gemm1 = [&](uint32_t (&d)[NCH / 4], int c) {
            WH<NCH>::first(d, a1[0][0], a1[0][1], a1[0][2], a1[0][3], descW1 + (uint64_t)(c * 768));
#pragma unroll
            for (int kk = 1; kk < 6; ++kk)
                WH<NCH>::acc(d, a1[kk][0], a1[kk][1], a1[kk][2], a1[kk][3], descW1 + (uint64_t)(c * 768 + kk * 128));
        };
        uint32_t b2a = sbase + OFF_B2I + q * 16;
        asm volatile("" : "+r"(b2a));
        auto init_acc = [&]() {
#pragma unroll
            for (int m = 0; m < 6; ++m) {
                const uint4 v = lds128(b2a + m * 64);
                acc2[4 * m] = v.x; acc2[4 * m + 1] = v.y; acc2[4 * m + 2] = v.z; acc2[4 * m + 3] = v.w;
            }
        };

        mbar_wait(bars + 8 * (BAR_DONE + wg), 0);
        load_a();
        TL(104);
#pragma unroll
        for (int i = 0; i < 4; ++i) partial_a(i);
        wg_fence();
        reduce_a();
        wg_commit();
        wg_wait<0>();
        fence_regs(st);
        norm_a();
        TL(105);
        __syncwarp();
        if (elect_one()) {
            mbar_arrive(bars + 8 * (BAR_A_EMPTY + (wg & 1)));
            if (TOKPOS >= 80) mbar_arrive(bars + 8 * (BAR_DONE + wg + 1));
        }
        wg_fence();
        gemm1(h[0], 0);
        wg_commit();
        wg_wait<0>();
        uint32_t y[24];
#pragma unroll
        for (int i = 0; i < 24; ++i) y[i] = 0;
        auto flush_y = [&](__nv_bfloat16* p) {
#pragma unroll
            for (int jj = 0; jj < 3; ++jj)
#pragma unroll
                for (int hrow = 0; hrow < 2; ++hrow)
                    red_add_bf16x8(p + hrow * 8 * CH + jj * 32, y[jj * 8 + hrow], y[jj * 8 + hrow + 2], y[jj * 8 + hrow + 4], y[jj * 8 + hrow + 6]);
        };
        __nv_bfloat16* optr = out + ((ys + dir * (wg + 1 - (UNC ? 0 : NMLP))) * IMG_W + strip * STRIP_W + wr * 16 + g) * CH + q * 8;
#pragma unroll 1
        for (int t = wg; t < ROWS_PER_CTA; t += NMLP) {
            TL(4 + 2 * (t / NMLP));
            const bool more = t + NMLP < ROWS_PER_CTA;
            const uint32_t nbar = bars + 8 * (BAR_DONE + ((t + NMLP) & 3)), nph = ((t + NMLP) >> 2) & 1;
            bool ready = true;
            SCHED_FENCE();
            constexpr int P = NCH / 4, NP = HID / 4;
            uint32_t zz[3];
            uint16_t t0[LB], t1[LB];
#pragma unroll
            for (int G = 0; G <= NP + LAG; ++G) {
                const int ca = G / P;
                if (G == NP - P - TESTPOS) ready = mbar_test(nbar, nph) || !more;
                if (G == NP - P && !ready) mbar_wait(nbar, nph);
                if (G % P == 0 && ca >= 1 && G < NP) { wg_wait<0>(); fence_regs(h[ca & 1]); }
                if (G == NP - P) load_a();
                if (G == STATPOS) {
                    wg_fence();
                    reduce_a();
                    wg_commit();
                    if (more && elect_one()) mbar_arrive(bars + 8 * (BAR_A_EMPTY + ((t + NMLP) & 1)));
                }
                if (G >= P + LAG && (G - LAG) % P == 0) {
                    const int c = (G - LAG) / P - 1;
                    fence_regs(h[c & 1]);
                    wg_fence();
#pragma unroll
                    for (int kk = 0; kk < NCH / 16; ++kk)
                        WH<96>::acc(acc2, h[c & 1][kk * 4], h[c & 1][kk * 4 + 1], h[c & 1][kk * 4 + 2], h[c & 1][kk * 4 + 3],
                                    descW2 + (uint64_t)(((c * (NCH / 8) + 2 * kk) * (CH / 8)) * 8));
                    wg_commit();
                }
                if (G % P == (ca == 0 ? 1 : G1POS) && ca + 1 < NCHUNK) {
                    if (ca > 0) wg_wait<0>();
                    wg_fence();
                    gemm1(h[(ca + 1) & 1], ca + 1);
                    wg_commit();
                }
                if (G == INITPOS) init_acc();
                if (G == TOKPOS && G < NP - P && elect_one()) mbar_arrive(bars + 8 * (BAR_DONE + ((t + 1) & 3)));
                if (G == TOKPOS && G >= NP - P && elect_one()) mbar_arrive(bars + 8 * (BAR_DONE + ((t + NMLP + 1) & 3)));
                if (G >= REDPOS && G < REDPOS + 6 * REDSTEP && (G - REDPOS) % REDSTEP == 0) {
                    const int jj = (G - REDPOS) / REDSTEP / 2, hrow = (G - REDPOS) / REDSTEP % 2;
                    red_add_bf16x8_if(UNC || t != wg, optr + hrow * 8 * CH + jj * 32, y[jj * 8 + hrow], y[jj * 8 + hrow + 2], y[jj * 8 + hrow + 4], y[jj * 8 + hrow + 6]);
                }
                if (G == 3 * P + 4) {
                    static_assert(NMLP & 1, "slot alternates");
                    asm volatile("add.u32 %0, %0, %1;" : "+r"(la) : "r"((t & 1) ? -A_BYTES : A_BYTES));
                    asm volatile("add.u64 %0, %0, %1;" : "+l"(optr) : "l"((UNC && t == wg) ? 0ll : (long long)dir * (NMLP * IMG_W * CH * 2)));
                }
                if (G >= STATPOS - 4 && G < STATPOS) partial_a(G - (STATPOS - 4));
                int e = G - LAG;
                if (e >= 0 && e < NP) {
                    uint32_t& v = h[(e / P) & 1][e % P];
                    uint32_t o;
                    asm volatile("{\n\t.reg .b32 t;\n\tmov.b32 t, {%2, %3};\n\tfma.rn.f16x2 %0, %1, t, %1;\n\t}"
                                 : "=r"(o) : "r"(v), "h"(t0[e % LB]), "h"(t1[e % LB]));
                    v = o;
                }
                e = G - 1;
                if (e >= 0 && e < NP)
                    asm volatile("{\n\t.reg .b16 l, h;\n\tmov.b32 {l, h}, %2;\n\ttanh.approx.f16 %0, l;\n\ttanh.approx.f16 %1, h;\n\t}"
                                 : "=h"(t0[e % LB]), "=h"(t1[e % LB]) : "r"(zz[e & 1]));
                if (G < NP)
                    asm volatile("{\n\t.reg .b32 p;\n\tfma.rn.f16x2 p, %1, %1, %2;\n\tmul.rn.f16x2 %0, %1, p;\n\t}"
                                 : "=r"(zz[G & 1]) : "r"(h[ca & 1][G % P]), "r"(0x40D940D9u));
                SCHED_FENCE();
            }
            wg_wait<1>();
            fence_regs(st);
            norm_a();
            if (TOKPOS == 100 && elect_one()) mbar_arrive(bars + 8 * (BAR_DONE + ((t + NMLP + 1) & 3)));
            wg_fence();
            gemm1(h[0], 0);
            wg_commit();
            SCHED_FENCE();
            wg_wait<1>();
            fence_regs(acc2);
            TL(5 + 2 * (t / NMLP));
#pragma unroll
            for (int i = 0; i < 24; ++i) y[i] = h2_to_bf2(acc2[i]);
            if (oscale != 0x3F803F80u) {
#pragma unroll
                for (int i = 0; i < 24; ++i) y[i] = hmul2_bf16(y[i], oscale);
            }
            wg_wait<0>();
        }
        flush_y(optr);
        CK_END();
    }
}

typedef CUresult (*PFN_encodeTiled)(CUtensorMap*, CUtensorMapDataType, cuuint32_t, void*, const cuuint64_t*,
                                    const cuuint64_t*, const cuuint32_t*, const cuuint32_t*, CUtensorMapInterleave,
                                    CUtensorMapSwizzle, CUtensorMapL2promotion, CUtensorMapFloatOOBfill);

}

extern "C" void kernel_launch(void* const* d_in, const int* in_sizes, int n_in, void* d_out, int out_size) {
    const __nv_bfloat16* x = (const __nv_bfloat16*)d_in[0];
    const __nv_bfloat16* dw = (const __nv_bfloat16*)d_in[1];
    const __nv_bfloat16* w1 = (const __nv_bfloat16*)d_in[2];
    const __nv_bfloat16* b1 = (const __nv_bfloat16*)d_in[3];
    const __nv_bfloat16* w2 = (const __nv_bfloat16*)d_in[4];
    const __nv_bfloat16* b2 = (const __nv_bfloat16*)d_in[5];
    const __nv_bfloat16* gamma = (const __nv_bfloat16*)d_in[6];
    __nv_bfloat16* out = (__nv_bfloat16*)d_out;

    static PFN_encodeTiled encode = nullptr;
    if (!encode) {
        void* fn = nullptr;
        cudaDriverEntryPointQueryResult qres;
        cudaGetDriverEntryPoint("cuTensorMapEncodeTiled", &fn, cudaEnableDefault, &qres);
        encode = (PFN_encodeTiled)fn;
        cudaFuncSetAttribute(convnext_fused_kernel, cudaFuncAttributeMaxDynamicSharedMemorySize, SMEM_BYTES);
    }
    CUtensorMap xmap, w1map;
    cuuint64_t gdim[3] = {CH, IMG_W, IMG_H};
    cuuint64_t gstr[2] = {CH * 2, (cuuint64_t)IMG_W * CH * 2};
    cuuint32_t box[3] = {CH, HALF_W, 1};
    cuuint32_t estr[3] = {1, 1, 1};
    encode(&xmap, CU_TENSOR_MAP_DATA_TYPE_BFLOAT16, 3, (void*)x, gdim, gstr, box, estr, CU_TENSOR_MAP_INTERLEAVE_NONE,
           CU_TENSOR_MAP_SWIZZLE_NONE, XPROMO, CU_TENSOR_MAP_FLOAT_OOB_FILL_NONE);
    cuuint64_t wdim[2] = {HID, CH};
    cuuint64_t wstr[1] = {HID * 2};
    cuuint32_t wbox[2] = {NCH, CH};
    encode(&w1map, CU_TENSOR_MAP_DATA_TYPE_BFLOAT16, 2, (void*)w1, wdim, wstr, wbox, estr, CU_TENSOR_MAP_INTERLEAVE_NONE,
           CU_TENSOR_MAP_SWIZZLE_128B, CU_TENSOR_MAP_L2_PROMOTION_L2_256B, CU_TENSOR_MAP_FLOAT_OOB_FILL_NONE);

    convnext_fused_kernel<<<NUM_CTAS, NUM_THREADS, SMEM_BYTES>>>(xmap, w1map, dw, w1, b1, w2, b2, gamma, out, 0u);
}
```

```cpp
#include <cuda_runtime.h>
#include <cuda_bf16.h>
#include <cuda.h>
#include <stdint.h>

namespace {

constexpr int IMG_H = 512, IMG_W = 512, CH = 96, HID = 384;
constexpr int STRIP_W = 64;
constexpr int NUM_STRIPS = IMG_W / STRIP_W;
constexpr int ROWS_PER_CTA = 32;
constexpr int NUM_CTAS = NUM_STRIPS * (IMG_H / ROWS_PER_CTA);
constexpr int HALF_W = STRIP_W / 2 + 3;
constexpr int HALF_BYTES = HALF_W * CH * 2;
constexpr int HALF_BOX = ((HALF_BYTES + 127) / 128) * 128;
constexpr int HALF_OFF = HALF_BOX + CH * 2;
constexpr int ROW_BYTES = 2 * HALF_BOX;
constexpr int NROW = 4;
#define RMLP 128
#define RCONV (512 - 3 * RMLP)
#define LAG 3
#define LB LAG
#define STG 3
#define G1POS 10
#define STATPOS 94
#define UNC 1
#define REDPOS 8
#define REDSTEP 6
#define INITPOS 2
#define TESTPOS 4
#define XPROMO CU_TENSOR_MAP_L2_PROMOTION_L2_128B
#define TOKPOS 100
#define WMASK 0xffffffffu
#define EARLYREF 1
#define EARLYE 1
#define MORE 1
#define TOKB 0
#define RESID 0
#define LDPOS 2
#define LDDIST 12
#define DRY 0
#define XJ(j) (j)
#define RELPOS 94
#define EARLYX 0
#define REDEF 0
#define EFT 99
#define NE 0
#define G2EPOS 11
#define G2P0 13
#define G2P1 13
#define G2P2 19
#define G2P3 19
#define G1PA 7
#define G1PB 10
#define G1N 3
#define G2C(p, prev) ((p) >= G1PB && (p) < 16 && (p) != (prev))
#define G2INFL (G2C(G2P0, -1) + G2C(G2P1, G2P0) + G2C(G2P2, G2P1))
static_assert(G2P0 >= 7 && G2P1 >= 11 && G2P2 >= 15 && G2P3 == 19 && G2P0 >= G1PA, "schedule");
#define ORDER "Ad012b3"
#define NROW0 1
#define NROW1 3
#define PF0 0
constexpr int NA = 2;
constexpr int A_PITCH = CH * 2 + 16;
constexpr int A_HALF = 32 * A_PITCH + 64;
constexpr int A_BYTES = ((A_HALF + 32 * A_PITCH + 127) / 128) * 128;
constexpr int NCH = 64;
constexpr int NCHUNK = HID / NCH;
#define SPLIT_ 2
#define PSPLIT 11
#define FSPLIT 10
constexpr int SPLIT = SPLIT_;
constexpr int NMLP = 3;

constexpr int OFF_W1 = 0;
constexpr int OFF_W2 = OFF_W1 + CH * HID * 2;
constexpr int OFF_ROW = OFF_W2 + CH * HID * 2;
constexpr int OFF_A = OFF_ROW + NROW * ROW_BYTES;
constexpr int OFF_ONES = OFF_A + NA * A_BYTES;
constexpr int OFF_B2I = OFF_ONES + 512;
constexpr int OFF_MAX = OFF_B2I + 384;
constexpr int OFF_DW = OFF_MAX + 128;
constexpr int OFF_BAR = OFF_DW + 9 * CH * 2;
constexpr int BAR_ROW_FULL = 0, BAR_DONE = NROW, BAR_PRIME = BAR_DONE + NMLP, BAR_FREE = BAR_PRIME + 1, BAR_A_EMPTY = BAR_FREE + 2;
constexpr int BAR_W1 = BAR_A_EMPTY + NA, BAR_W2 = BAR_W1 + NCHUNK, BAR_DW = BAR_W2 + 4;
constexpr int BAR_W1RDY = BAR_DW + 1, BAR_W2RDY = BAR_W1RDY + 1;
constexpr int NUM_BARS = BAR_W2RDY + 1;
constexpr int SMEM_BYTES = OFF_BAR + NUM_BARS * 8;
static_assert(SMEM_BYTES <= 232448, "smem");
static_assert(HALF_OFF % 128 == 64 && OFF_ROW % 128 == 0 && OFF_ONES % 128 == 0, "bank layout");

constexpr int NUM_THREADS = 128 * (NMLP + 1);

constexpr float GELU_A = 0.7978845608028654f / 2.423828125f;
constexpr float GELU_INV2A = 0.5f / GELU_A;

__device__ __forceinline__ uint32_t smem_u32(const void* p) { return (uint32_t)__cvta_generic_to_shared(p); }

__device__ __forceinline__ void mbar_init(uint32_t bar, uint32_t count) {
    asm volatile("mbarrier.init.shared::cta.b64 [%0], %1;" ::"r"(bar), "r"(count) : "memory");
}
__device__ __forceinline__ void mbar_expect_tx(uint32_t bar, uint32_t bytes) {
    asm volatile("mbarrier.arrive.expect_tx.shared::cta.b64 _, [%0], %1;" ::"r"(bar), "r"(bytes) : "memory");
}
__device__ __forceinline__ void mbar_arrive(uint32_t bar) {
    asm volatile("mbarrier.arrive.shared::cta.b64 _, [%0];" ::"r"(bar) : "memory");
}
__device__ __forceinline__ bool mbar_try(uint32_t bar, uint32_t parity) {
    uint32_t done;
    asm volatile(
        "{\n\t.reg .pred p;\n\t"
        "mbarrier.try_wait.parity.shared::cta.b64 p, [%1], %2;\n\t"
        "selp.u32 %0, 1, 0, p;\n\t}"
        : "=r"(done) : "r"(bar), "r"(parity) : "memory");
    return done != 0;
}
__device__ __forceinline__ bool mbar_test(uint32_t bar, uint32_t parity) {
    uint32_t done;
    asm volatile(
        "{\n\t.reg .pred p;\n\t"
        "mbarrier.test_wait.parity.shared::cta.b64 p, [%1], %2;\n\t"
        "selp.u32 %0, 1, 0, p;\n\t}"
        : "=r"(done) : "r"(bar), "r"(parity) : "memory");
    return done != 0;
}
__device__ __forceinline__ void mbar_wait(uint32_t bar, uint32_t parity) {
    for (int it = 0; it < (1 << 20); ++it)
        if (mbar_try(bar, parity)) break;
}
__device__ __forceinline__ uint64_t policy_evict_first() {
    uint64_t p;
    asm("createpolicy.fractional.L2::evict_first.b64 %0, 1.0;" : "=l"(p));
    return p;
}
__device__ __forceinline__ void tma_load_3d(uint32_t dst, const CUtensorMap* map, uint32_t bar, int c0, int c1, int c2) {
    asm volatile(
        "cp.async.bulk.tensor.3d.shared::cluster.global.mbarrier::complete_tx::bytes.L2::cache_hint [%0], [%1, {%3, %4, %5}], [%2], %6;"
        ::"r"(dst), "l"(reinterpret_cast<uint64_t>(map)), "r"(bar), "r"(c0), "r"(c1), "r"(c2), "l"(policy_evict_first()) : "memory");
}
__device__ __forceinline__ void tma_load_2d(uint32_t dst, const CUtensorMap* map, uint32_t bar, int c0, int c1) {
    asm volatile(
        "cp.async.bulk.tensor.2d.shared::cluster.global.mbarrier::complete_tx::bytes [%0], [%1, {%3, %4}], [%2];"
        ::"r"(dst), "l"(reinterpret_cast<uint64_t>(map)), "r"(bar), "r"(c0), "r"(c1) : "memory");
}
__device__ __forceinline__ bool elect_one() {
    uint32_t p;
    asm volatile("{\n\t.reg .pred p;\n\telect.sync _|p, 0xffffffff;\n\tselp.u32 %0, 1, 0, p;\n\t}" : "=r"(p));
    return p != 0;
}
__device__ __forceinline__ void bulk_load(uint32_t dst, const void* src, uint32_t bytes, uint32_t bar) {
    asm volatile("cp.async.bulk.shared::cluster.global.mbarrier::complete_tx::bytes [%0], [%1], %2, [%3];"
                 ::"r"(dst), "l"(src), "r"(bytes), "r"(bar) : "memory");
}
__device__ __forceinline__ void bulk_store(void* dst, uint32_t src, uint32_t bytes) {
    asm volatile("cp.async.bulk.global.shared::cta.bulk_group [%0], [%1], %2;" ::"l"(dst), "r"(src), "r"(bytes) : "memory");
}
__device__ __forceinline__ void bulk_commit() { asm volatile("cp.async.bulk.commit_group;" ::: "memory"); }
template <int N> __device__ __forceinline__ void bulk_wait_read() {
    asm volatile("cp.async.bulk.wait_group.read %0;" ::"n"(N) : "memory");
}
template <int N> __device__ __forceinline__ void bulk_wait() {
    asm volatile("cp.async.bulk.wait_group %0;" ::"n"(N) : "memory");
}
__device__ __forceinline__ void ldsm_x4(uint32_t addr, uint32_t& r0, uint32_t& r1, uint32_t& r2, uint32_t& r3) {
    asm volatile("ldmatrix.sync.aligned.m8n8.x4.shared.b16 {%0,%1,%2,%3}, [%4];"
                 : "=r"(r0), "=r"(r1), "=r"(r2), "=r"(r3) : "r"(addr) : "memory");
}
__device__ __forceinline__ void ldsm_x2(uint32_t addr, uint32_t& r0, uint32_t& r1) {
    asm volatile("ldmatrix.sync.aligned.m8n8.x2.shared.b16 {%0,%1}, [%2];" : "=r"(r0), "=r"(r1) : "r"(addr) : "memory");
}
__device__ __forceinline__ void stsm_x4(uint32_t addr, uint32_t r0, uint32_t r1, uint32_t r2, uint32_t r3) {
    asm volatile("stmatrix.sync.aligned.m8n8.x4.shared.b16 [%0], {%1,%2,%3,%4};"
                 ::"r"(addr), "r"(r0), "r"(r1), "r"(r2), "r"(r3) : "memory");
}
__device__ __forceinline__ uint4 lds128(uint32_t addr) {
    uint4 v;
    asm volatile("ld.shared.v4.u32 {%0,%1,%2,%3}, [%4];" : "=r"(v.x), "=r"(v.y), "=r"(v.z), "=r"(v.w) : "r"(addr) : "memory");
    return v;
}
__device__ __forceinline__ uint32_t lds32(uint32_t addr) {
    uint32_t a;
    asm volatile("ld.shared.u32 %0, [%1];" : "=r"(a) : "r"(addr) : "memory");
    return a;
}
__device__ __forceinline__ void sts32(uint32_t addr, uint32_t a) {
    asm volatile("st.shared.u32 [%0], %1;" ::"r"(addr), "r"(a) : "memory");
}
__device__ __forceinline__ void sts128(uint32_t addr, uint32_t a, uint32_t b, uint32_t c, uint32_t d) {
    asm volatile("st.shared.v4.u32 [%0], {%1,%2,%3,%4};" ::"r"(addr), "r"(a), "r"(b), "r"(c), "r"(d) : "memory");
}
__device__ __forceinline__ uint32_t hfma2_bf16(uint32_t a, uint32_t b, uint32_t c) {
    uint32_t d;
    asm("fma.rn.bf16x2 %0, %1, %2, %3;" : "=r"(d) : "r"(a), "r"(b), "r"(c));
    return d;
}
__device__ __forceinline__ uint32_t hmul2_bf16(uint32_t a, uint32_t b) {
    uint32_t d;
    asm("mul.rn.bf16x2 %0, %1, %2;" : "=r"(d) : "r"(a), "r"(b));
    return d;
}
__device__ __forceinline__ uint32_t hadd2_bf16(uint32_t a, uint32_t b) {
    uint32_t d;
    asm("add.rn.bf16x2 %0, %1, %2;" : "=r"(d) : "r"(a), "r"(b));
    return d;
}
__device__ __forceinline__ float bf_lo(uint32_t v) { return __uint_as_float(v << 16); }
__device__ __forceinline__ float bf_hi(uint32_t v) { return __uint_as_float(v & 0xffff0000u); }
__device__ __forceinline__ uint32_t pack_bf16(float lo, float hi) {
    uint32_t d;
    asm("cvt.rn.bf16x2.f32 %0, %1, %2;" : "=r"(d) : "f"(hi), "f"(lo));
    return d;
}
__device__ __forceinline__ uint32_t pack_f16(float lo, float hi) {
    uint32_t d;
    asm("cvt.rn.f16x2.f32 %0, %1, %2;" : "=r"(d) : "f"(hi), "f"(lo));
    return d;
}
__device__ __forceinline__ uint32_t scale2h(uint32_t v, float s) {
    return pack_f16(bf_lo(v) * s, bf_hi(v) * s);
}
__device__ __forceinline__ uint32_t h2_to_bf2(uint32_t v) {
    uint32_t d;
    asm("{\n\t.reg .b16 l, h;\n\t.reg .f32 a, b;\n\tmov.b32 {l, h}, %1;\n\tcvt.f32.f16 a, l;\n\tcvt.f32.f16 b, h;\n\t"
        "cvt.rn.bf16x2.f32 %0, b, a;\n\t}" : "=r"(d) : "r"(v));
    return d;
}
__device__ __forceinline__ uint32_t hsub2_f16(uint32_t a, uint32_t b) {
    uint32_t d;
    asm("sub.rn.f16x2 %0, %1, %2;" : "=r"(d) : "r"(a), "r"(b));
    return d;
}
__device__ __forceinline__ uint32_t hmul2_f16(uint32_t a, uint32_t b) {
    uint32_t d;
    asm("mul.rn.f16x2 %0, %1, %2;" : "=r"(d) : "r"(a), "r"(b));
    return d;
}
__device__ __forceinline__ uint32_t bf2_to_h2(uint32_t y) { return (y & 0x7fff7fffu) * 7u + y; }
__device__ __forceinline__ uint32_t absmax2(uint32_t m, uint32_t v) { return __vmaxu2(m, v & 0x7fff7fffu); }
__device__ __forceinline__ void red_add_bf16x8(void* p, uint32_t a, uint32_t b, uint32_t c, uint32_t d) {
    asm volatile("red.global.add.noftz.v4.bf16x2 [%0], {%1,%2,%3,%4};" ::"l"(p), "r"(a), "r"(b), "r"(c), "r"(d) : "memory");
}
__device__ __forceinline__ uint64_t policy_evict_normal() {
    uint64_t p;
    asm("createpolicy.fractional.L2::evict_normal.b64 %0, 1.0;" : "=l"(p));
    return p;
}
__device__ __forceinline__ void red_add_bf16x8_pol(void* p, uint32_t a, uint32_t b, uint32_t c, uint32_t d, uint64_t pol) {
    asm volatile("red.global.add.noftz.L2::cache_hint.v4.bf16x2 [%0], {%1,%2,%3,%4}, %5;" ::"l"(p), "r"(a), "r"(b), "r"(c), "r"(d), "l"(pol) : "memory");
}
__device__ __forceinline__ void red_add_bf16x8_if(bool pr, void* p, uint32_t a, uint32_t b, uint32_t c, uint32_t d) {
    asm volatile("{\n\t.reg .pred p;\n\tsetp.ne.u32 p, %5, 0;\n\t@p red.global.add.noftz.v4.bf16x2 [%0], {%1,%2,%3,%4};\n\t}"
                 ::"l"(p), "r"(a), "r"(b), "r"(c), "r"(d), "r"((uint32_t)pr) : "memory");
}
__device__ __forceinline__ uint4 ldg_stream(const void* p) {
    uint4 v;
    asm volatile("ld.global.nc.L1::no_allocate.L2::cache_hint.v4.u32 {%0,%1,%2,%3}, [%4], %5;"
                 : "=r"(v.x), "=r"(v.y), "=r"(v.z), "=r"(v.w) : "l"(p), "l"(policy_evict_first()) : "memory");
    return v;
}
__device__ __forceinline__ void stg128(void* p, uint32_t a, uint32_t b, uint32_t c, uint32_t d) {
    asm volatile("st.global.v4.u32 [%0], {%1,%2,%3,%4};" ::"l"(p), "r"(a), "r"(b), "r"(c), "r"(d) : "memory");
}
__device__ __forceinline__ uint32_t gelu2x(uint32_t v) {
    uint32_t p, z, t, g;
    asm("fma.rn.f16x2 %0, %1, %1, %2;" : "=r"(p) : "r"(v), "r"(0x40D940D9u));
    asm("mul.rn.f16x2 %0, %1, %2;" : "=r"(z) : "r"(v), "r"(p));
    asm("tanh.approx.f16x2 %0, %1;" : "=r"(t) : "r"(z));
    asm("fma.rn.f16x2 %0, %1, %2, %1;" : "=r"(g) : "r"(v), "r"(t));
    return g;
}
__device__ __forceinline__ void wg_fence() { asm volatile("wgmma.fence.sync.aligned;" ::: "memory"); }
__device__ __forceinline__ void wg_commit() { asm volatile("wgmma.commit_group.sync.aligned;" ::: "memory"); }
template <int N> __device__ __forceinline__ void wg_wait() {
    asm volatile("wgmma.wait_group.sync.aligned %0;" ::"n"(N) : "memory");
}
template <int N> __device__ __forceinline__ void fence_regs(float (&d)[N]) {
#pragma unroll
    for (int i = 0; i < N; ++i) asm volatile("" : "+f"(d[i])::"memory");
}
template <int N> __device__ __forceinline__ void fence_regs(uint32_t (&d)[N]) {
#pragma unroll
    for (int i = 0; i < N; ++i) asm volatile("" : "+r"(d[i])::"memory");
}

template <int N> struct WH;
template <> struct WH<64> {
    static __device__ __forceinline__ void acc(uint32_t* d, uint32_t a0, uint32_t a1, uint32_t a2, uint32_t a3, uint64_t desc) {
        asm volatile("wgmma.mma_async.sync.aligned.m64n64k16.f16.f16.f16 {%0,%1,%2,%3,%4,%5,%6,%7,%8,%9,%10,%11,%12,%13,%14,%15}, "
                     "{%16,%17,%18,%19}, %20, 1, 1, 1, 1;"
                     : "+r"(d[0]), "+r"(d[1]), "+r"(d[2]), "+r"(d[3]), "+r"(d[4]), "+r"(d[5]), "+r"(d[6]), "+r"(d[7]), "+r"(d[8]), "+r"(d[9]), "+r"(d[10]), "+r"(d[11]), "+r"(d[12]), "+r"(d[13]), "+r"(d[14]), "+r"(d[15])
                     : "r"(a0), "r"(a1), "r"(a2), "r"(a3), "l"(desc) : "memory");
    }
    static __device__ __forceinline__ void first(uint32_t* d, uint32_t a0, uint32_t a1, uint32_t a2, uint32_t a3, uint64_t desc) {
        asm volatile("wgmma.mma_async.sync.aligned.m64n64k16.f16.f16.f16 {%0,%1,%2,%3,%4,%5,%6,%7,%8,%9,%10,%11,%12,%13,%14,%15}, "
                     "{%16,%17,%18,%19}, %20, 0, 1, 1, 1;"
                     : "=r"(d[0]), "=r"(d[1]), "=r"(d[2]), "=r"(d[3]), "=r"(d[4]), "=r"(d[5]), "=r"(d[6]), "=r"(d[7]), "=r"(d[8]), "=r"(d[9]), "=r"(d[10]), "=r"(d[11]), "=r"(d[12]), "=r"(d[13]), "=r"(d[14]), "=r"(d[15])
                     : "r"(a0), "r"(a1), "r"(a2), "r"(a3), "l"(desc) : "memory");
    }
};
template <> struct WH<96> {
    static __device__ __forceinline__ void acc(uint32_t* d, uint32_t a0, uint32_t a1, uint32_t a2, uint32_t a3, uint64_t desc) {
        asm volatile("wgmma.mma_async.sync.aligned.m64n96k16.f16.f16.f16 {%0,%1,%2,%3,%4,%5,%6,%7,%8,%9,%10,%11,%12,%13,%14,%15,%16,%17,%18,%19,%20,%21,%22,%23}, "
                     "{%24,%25,%26,%27}, %28, 1, 1, 1, 1;"
                     : "+r"(d[0]), "+r"(d[1]), "+r"(d[2]), "+r"(d[3]), "+r"(d[4]), "+r"(d[5]), "+r"(d[6]), "+r"(d[7]), "+r"(d[8]), "+r"(d[9]), "+r"(d[10]), "+r"(d[11]), "+r"(d[12]), "+r"(d[13]), "+r"(d[14]), "+r"(d[15]), "+r"(d[16]), "+r"(d[17]), "+r"(d[18]), "+r"(d[19]), "+r"(d[20]), "+r"(d[21]), "+r"(d[22]), "+r"(d[23])
                     : "r"(a0), "r"(a1), "r"(a2), "r"(a3), "l"(desc) : "memory");
    }
    static __device__ __forceinline__ void first(uint32_t* d, uint32_t a0, uint32_t a1, uint32_t a2, uint32_t a3, uint64_t desc) {
        asm volatile("wgmma.mma_async.sync.aligned.m64n96k16.f16.f16.f16 {%0,%1,%2,%3,%4,%5,%6,%7,%8,%9,%10,%11,%12,%13,%14,%15,%16,%17,%18,%19,%20,%21,%22,%23}, "
                     "{%24,%25,%26,%27}, %28, 0, 1, 1, 1;"
                     : "=r"(d[0]), "=r"(d[1]), "=r"(d[2]), "=r"(d[3]), "=r"(d[4]), "=r"(d[5]), "=r"(d[6]), "=r"(d[7]), "=r"(d[8]), "=r"(d[9]), "=r"(d[10]), "=r"(d[11]), "=r"(d[12]), "=r"(d[13]), "=r"(d[14]), "=r"(d[15]), "=r"(d[16]), "=r"(d[17]), "=r"(d[18]), "=r"(d[19]), "=r"(d[20]), "=r"(d[21]), "=r"(d[22]), "=r"(d[23])
                     : "r"(a0), "r"(a1), "r"(a2), "r"(a3), "l"(desc) : "memory");
    }
};

__device__ __forceinline__ void wgmma_stat_first(float (&d)[4], const uint32_t (&a)[4], uint64_t desc) {
    asm volatile("wgmma.mma_async.sync.aligned.m64n8k16.f32.bf16.bf16 {%0,%1,%2,%3}, {%4,%5,%6,%7}, %8, 0, 1, 1, 1;"
                 : "=f"(d[0]), "=f"(d[1]), "=f"(d[2]), "=f"(d[3]) : "r"(a[0]), "r"(a[1]), "r"(a[2]), "r"(a[3]), "l"(desc) : "memory");
}
__device__ __forceinline__ void wgmma_stat_acc(float (&d)[4], const uint32_t (&a)[4], uint64_t desc) {
    asm volatile("wgmma.mma_async.sync.aligned.m64n8k16.f32.bf16.bf16 {%0,%1,%2,%3}, {%4,%5,%6,%7}, %8, 1, 1, 1, 1;"
                 : "+f"(d[0]), "+f"(d[1]), "+f"(d[2]), "+f"(d[3]) : "r"(a[0]), "r"(a[1]), "r"(a[2]), "r"(a[3]), "l"(desc) : "memory");
}

__device__ __forceinline__ uint64_t make_desc(uint32_t addr, uint32_t lbo, uint32_t sbo) {
    return (uint64_t)((addr & 0x3FFFF) >> 4) | ((uint64_t)(lbo >> 4) << 16) | ((uint64_t)(sbo >> 4) << 32);
}

#define CK_BEGIN()
#define CK_END()
#define TL(slot)

#define SCHED_FENCE() asm volatile("{\n\t.reg .pred p;\n\tsetp.ne.u32 p, %0, 0;\n\t@p exit;\n\t}" ::"r"(zero) : "memory")

__global__ void __launch_bounds__(NUM_THREADS, 1)
convnext_fused_kernel(const __grid_constant__ CUtensorMap xmap, const __grid_constant__ CUtensorMap w1map,
                      const __nv_bfloat16* __restrict__ dw, const __nv_bfloat16* __restrict__ w1,
                      const __nv_bfloat16* __restrict__ b1, const __nv_bfloat16* __restrict__ w2,
                      const __nv_bfloat16* __restrict__ b2, const __nv_bfloat16* __restrict__ gamma,
                      __nv_bfloat16* __restrict__ out, long long xdiff, uint32_t zero) {
    extern __shared__ __align__(1024) uint8_t smem[];
    const uint32_t sbase = smem_u32(smem);
    const int tid = threadIdx.x;
    const int warp = __shfl_sync(0xffffffffu, tid >> 5, 0);
    const int lane = tid & 31;
    const int wg = warp >> 2, wr = warp & 3;
    const uint32_t bars = sbase + OFF_BAR;
    const int strip = blockIdx.x % NUM_STRIPS;
    const int band = blockIdx.x / NUM_STRIPS;
    const int dir = (band & 1) ? 1 : -1;
    const int ys = (band & 1) ? band * ROWS_PER_CTA - 1 : (band + 1) * ROWS_PER_CTA;
    TL(0);
    CK_BEGIN();

    auto load_row = [&](int j) {
        const uint32_t bar = bars + 8 * (BAR_ROW_FULL + (j & 3));
        const uint32_t dst = sbase + OFF_ROW + (j & 3) * ROW_BYTES;
        mbar_expect_tx(bar, 2 * HALF_BYTES);
        tma_load_3d(dst, &xmap, bar, 0, strip * STRIP_W - 1, ys + dir * j);
        tma_load_3d(dst + HALF_BOX, &xmap, bar, 0, strip * STRIP_W + 30, ys + dir * j);
    };
    auto load_w2 = [&](int s) {
        mbar_expect_tx(bars + 8 * (BAR_W2 + s), CH * HID / 2);
        bulk_load(sbase + OFF_W2 + s * (CH * HID / 2), w2 + s * (CH * HID / 4), CH * HID / 2, bars + 8 * (BAR_W2 + s));
    };
    if (warp == 11) {
        if (elect_one()) {
            for (int s = 0; s < NUM_BARS; ++s) mbar_init(bars + 8 * s, (s >= BAR_DONE && s < BAR_W1) ? (TOKPOS >= 0 && s < BAR_PRIME ? 8 : 4) : s == BAR_W1RDY ? 4 * NMLP : s == BAR_W2RDY ? 8 : 1);
            if (TOKPOS >= 0) asm volatile("mbarrier.arrive.shared::cta.b64 _, [%0], 4;" ::"r"(bars + 8 * BAR_DONE) : "memory");
            asm volatile("fence.mbarrier_init.release.cluster;" ::: "memory");
        }
        __syncwarp();
        asm volatile("bar.arrive 2, %0;" ::"n"(NUM_THREADS) : "memory");
        if (elect_one()) {
            constexpr char order[] = ORDER;
#pragma unroll
            for (int i = 0; i < 7; ++i) {
                if (order[i] == 'A') {
#pragma unroll 1
                    for (int s = 0; s < NCHUNK; ++s) {
                        mbar_expect_tx(bars + 8 * (BAR_W1 + s), CH * NCH * 2);
                        tma_load_2d(sbase + OFF_W1 + s * (CH * NCH * 2), &w1map, bars + 8 * (BAR_W1 + s), s * NCH, 0);
                    }
                } else if (order[i] == 'b') {
#pragma unroll 1
                    for (int s = 0; s < 4; ++s) load_w2(s);
                } else if (order[i] == 'd') {
                    mbar_expect_tx(bars + 8 * BAR_DW, 9 * CH * 2);
                    bulk_load(sbase + OFF_DW, dw, 9 * CH * 2, bars + 8 * BAR_DW);
                } else {
                    load_row(order[i] - '0');
                }
            }
        }
        __syncwarp();
    } else if (warp == 10) {
        if (elect_one()) asm volatile("prefetch.tensormap [%0];" ::"l"(reinterpret_cast<uint64_t>(&xmap)) : "memory");
    }
    TL(80);

    if (wg == NMLP) {
        asm volatile("setmaxnreg.dec.sync.aligned.u32 %0;" ::"n"(RCONV));
        asm volatile("bar.sync 2, %0;" ::"n"(NUM_THREADS) : "memory");
        uint32_t w[3][3][3];
        {
            mbar_wait(bars + 8 * BAR_DW, 0);
            const uint32_t wp = sbase + OFF_DW + 48 * ((wr + (lane >> 2)) & 3) + 4 * (lane & 3) + 3 * (CH * 2);
#pragma unroll
            for (int s = 0; s < 3; ++s)
#pragma unroll
                for (int t = 0; t < 9; ++t) w[t / 3][t % 3][s] = lds32(wp + (t / 3 - 1) * dir * 3 * (CH * 2) + (t % 3) * (CH * 2) + s * 16);
        }
        const int ga = lane & 7, ja = lane >> 3;
        const uint32_t ip = sbase + OFF_ROW + (uint32_t)((ga >> 2) * HALF_OFF + (8 * (ga & 3) + ja) * (CH * 2) + 48 * ((wr + ga) & 3));
        const uint32_t op = sbase + OFF_A + (uint32_t)((ga >> 2) * A_HALF + (8 * (ga & 3) + ja) * A_PITCH + 48 * ((wr + ga) & 3));
        static_assert(NROW == 4 && NA == 2, "ring arithmetic");
        uint32_t P[2][3][8], f[10], c[8];
        auto feed = [&](int e, int s, int i) {
#pragma unroll
            for (int o = i - 2; o <= i; ++o) {
                if (o < 0 || o > 7) continue;
                const int jx = i - o;
                if (jx == 0) {
                    asm volatile("fma.rn.bf16x2 %0, %3, %4, %1;\n\tfma.rn.bf16x2 %2, %3, %5, %2;\n\tmul.rn.bf16x2 %1, %3, %6;"
                                 : "=&r"(c[o]), "+r"(P[e][s][o]), "+r"(P[e ^ 1][s][o])
                                 : "r"(f[i]), "r"(w[2][0][s]), "r"(w[1][0][s]), "r"(w[0][0][s]));
                } else {
                    asm volatile("fma.rn.bf16x2 %0, %3, %4, %0;\n\tfma.rn.bf16x2 %2, %3, %5, %2;\n\tfma.rn.bf16x2 %1, %3, %6, %1;"
                                 : "+r"(c[o]), "+r"(P[e][s][o]), "+r"(P[e ^ 1][s][o])
                                 : "r"(f[i]), "r"(w[2][XJ(jx)][s]), "r"(w[1][XJ(jx)][s]), "r"(w[0][XJ(jx)][s]));
                }
            }
        };
        constexpr int NSTEPS = ROWS_PER_CTA + 2;
        __nv_bfloat16* xo = out + ((ys + dir) * IMG_W + strip * STRIP_W + wr * 16) * CH;
        const uint32_t xs = sbase + OFF_ROW + (wr >> 1) * HALF_OFF + ((wr & 1) * 16 + 1) * (CH * 2);
        mbar_wait(bars + 8 * BAR_ROW_FULL, 0);
        TL(4);
#pragma unroll
        for (int r = 0; r < 2; ++r) {
            if (r == 1) {
                mbar_wait(bars + 8 * (BAR_ROW_FULL + 1), 0);
                if (!RESID && elect_one()) {
                    bulk_store(xo, xs + ROW_BYTES, 16 * CH * 2);
                    bulk_commit();
                }
            }
#pragma unroll
            for (int s = 0; s < 3; ++s) {
                ldsm_x4(ip + r * ROW_BYTES + s * 16, f[0], f[1], f[2], f[3]);
                ldsm_x4(ip + r * ROW_BYTES + s * 16 + 4 * (CH * 2), f[4], f[5], f[6], f[7]);
                ldsm_x2(ip + r * ROW_BYTES + s * 16 + 8 * (CH * 2), f[8], f[9]);
#pragma unroll
                for (int o = 0; o < 8; ++o) {
                    if (r == 1) P[0][s][o] = hfma2_bf16(f[o + 2], w[1][2][s], hfma2_bf16(f[o + 1], w[1][1][s], hfma2_bf16(f[o], w[1][0][s], P[0][s][o])));
                    P[r][s][o] = hfma2_bf16(f[o + 2], w[0][2][s], hfma2_bf16(f[o + 1], w[0][1][s], hmul2_bf16(f[o], w[0][0][s])));
                }
            }
        }
        __syncwarp();
        if (elect_one()) {
            bulk_wait_read<0>();
            mbar_arrive(bars + 8 * BAR_PRIME);
        }
        TL(5);
        mbar_wait(bars + 8 * (BAR_ROW_FULL + 2), 0);
        TL(6);
        if (EARLYX) {
            xo += dir * IMG_W * CH;
            if (elect_one()) bulk_store(xo, xs + 2 * ROW_BYTES, 16 * CH * 2);
            bulk_commit();
        }
        ldsm_x4(ip + 2 * ROW_BYTES, f[0], f[1], f[2], f[3]);
        ldsm_x4(ip + 2 * ROW_BYTES + 4 * (CH * 2), f[4], f[5], f[6], f[7]);
        ldsm_x2(ip + 2 * ROW_BYTES + 8 * (CH * 2), f[8], f[9]);
        uint32_t dbar = bars + 8 * BAR_DONE;
#pragma unroll 1
        for (int m = 0; m < ROWS_PER_CTA / 4; ++m) {
            const bool last = m + 1 == ROWS_PER_CTA / 4;
#pragma unroll
            for (int u = 0; u < 4; ++u) {
                const int j = 4 * m + u + 2;
                const int rs = (u + 2) & 3, ns = (u + 3) & 3;
                TL(4 + 6 * j + 0);
                const uint32_t ebar = bars + 8 * (BAR_A_EMPTY + (u & 1)), rbar = bars + 8 * (BAR_ROW_FULL + ns);
                const uint32_t eph = ((u >> 1) & 1) ^ 1, rph = (m + (u >= 1)) & 1;
                if (!EARLYX) {
                    xo += dir * IMG_W * CH;
                    if (!(u == 3 && last)) {
                        if (elect_one()) bulk_store(xo, xs + rs * ROW_BYTES, 16 * CH * 2);
                    }
                    bulk_commit();
                }
                bool ok = mbar_test(ebar, eph);
#pragma unroll
                for (int s = 0; s < 3; ++s) {
                    if (s == 2) ok = mbar_test(rbar, rph) || (u == 3 && last);
                    feed(u & 1, s, 0); feed(u & 1, s, 1); feed(u & 1, s, 2); feed(u & 1, s, 3);
                    if (s == 0) {
                        if (!ok) mbar_wait(ebar, eph);
                        TL(4 + 6 * j + 1);
                    }
                    const uint32_t nx = ip + (s == 2 ? ns : rs) * ROW_BYTES + ((s + 1) % 3) * 16;
                    const uint32_t ox = op + (u & 1) * A_BYTES + s * 16;
                    ldsm_x4(nx, f[0], f[1], f[2], f[3]);
                    SCHED_FENCE();
                    feed(u & 1, s, 4); feed(u & 1, s, 5);
                    stsm_x4(ox, c[0], c[1], c[2], c[3]);
                    feed(u & 1, s, 6); feed(u & 1, s, 7);
                    ldsm_x4(nx + 4 * (CH * 2), f[4], f[5], f[6], f[7]);
                    SCHED_FENCE();
                    feed(u & 1, s, 8); feed(u & 1, s, 9);
                    stsm_x4(ox + 4 * A_PITCH, c[4], c[5], c[6], c[7]);
                    ldsm_x2(nx + 8 * (CH * 2), f[8], f[9]);
                    SCHED_FENCE();
                }
                TL(4 + 6 * j + 4);
                if (!RESID) bulk_wait<0>();
                __syncwarp();
                if (elect_one()) {
                    mbar_arrive(dbar);
                    if (EARLYREF) mbar_arrive(bars + 8 * (BAR_FREE + (u & 1)));
                }
                dbar = dbar == bars + 8 * (BAR_DONE + NMLP - 1) ? bars + 8 * BAR_DONE : dbar + 8;
                if (wr == u && !last) {
                    mbar_wait(bars + 8 * (BAR_FREE + (u & 1)), (u >> 1) & 1);
                    if (elect_one()) load_row(j + 4);
                }
                TL(4 + 6 * j + 2);
                if (!ok) {
                    mbar_wait(rbar, rph);
                    ldsm_x4(ip + ns * ROW_BYTES, f[0], f[1], f[2], f[3]);
                    ldsm_x4(ip + ns * ROW_BYTES + 4 * (CH * 2), f[4], f[5], f[6], f[7]);
                    ldsm_x2(ip + ns * ROW_BYTES + 8 * (CH * 2), f[8], f[9]);
                }
                if (EARLYX) {
                    xo += dir * IMG_W * CH;
                    if (!(u >= 2 && last)) {
                        if (elect_one()) bulk_store(xo, xs + ns * ROW_BYTES, 16 * CH * 2);
                    }
                    bulk_commit();
                }
                TL(4 + 6 * j + 5);
            }
        }
    } else {
        const int g = lane >> 2, q = lane & 3;
        uint4 r95, bb, gm[3];
        uint32_t b2v, g2v;
        r95 = __ldg(reinterpret_cast<const uint4*>(w1 + 95 * HID + (warp >> 1) * NCH + (lane & 7) * 8));
        bb = __ldg(reinterpret_cast<const uint4*>(b1 + (warp >> 1) * NCH + (lane & 7) * 8));
        auto load_gamma = [&]() {
#pragma unroll
            for (int jj = 0; jj < 3; ++jj) gm[jj] = __ldg(reinterpret_cast<const uint4*>(gamma + jj * 32 + q * 8));
            b2v = g2v = 0;
            if (tid >= 128 && tid < 128 + CH / 2) {
                b2v = __ldg(reinterpret_cast<const uint32_t*>(b2) + tid - 128);
                g2v = __ldg(reinterpret_cast<const uint32_t*>(gamma) + tid - 128);
            }
        };
        load_gamma();
        auto transform_w2 = [&](int s, int pass) {
            const uint32_t w2b = sbase + OFF_W2 + (warp - 4) * 6 * (8 * CH * 2);
            const float up = __uint_as_float((uint32_t)(127 + s) << 23), sc = up * GELU_INV2A;
            uint32_t gh[12];
#pragma unroll
            for (int e = 0; e < 12; ++e) {
                const uint32_t gv = (e & 3) == 0 ? gm[e / 4].x : (e & 3) == 1 ? gm[e / 4].y : (e & 3) == 2 ? gm[e / 4].z : gm[e / 4].w;
                const float lo = bf_lo(gv) * sc * 0x1p-112f, hi = bf_hi(gv) * sc * 0x1p-112f;
                gh[e] = pack_bf16(lo, hi);
            }
            if (tid < 128 + CH / 2) {
                const uint32_t v2 = pack_f16(bf_lo(b2v) * bf_lo(g2v) * up, bf_hi(b2v) * bf_hi(g2v) * up);
                const uint32_t a = sbase + OFF_B2I + (((tid >> 4) & 3) * 2 + ((tid >> 1) & 1)) * 64 + ((tid >> 2) & 3) * 16 + (tid & 1) * 8;
                sts32(a, v2); sts32(a + 4, v2);
            }
            mbar_wait(bars + 8 * (BAR_W2 + (warp >> 1) - 2), pass);
            TL(101);
            uint4 v[3];
#pragma unroll
            for (int jj = 0; jj < 3; ++jj) v[jj] = lds128(w2b + g * (CH * 2) + jj * 64 + q * 16);
            uint32_t mu = 0, ms = 0;
#pragma unroll 1
            for (int i = 0; i < 6; ++i) {
                TL(110 + i);
                uint32_t o[12];
#pragma unroll
                for (int jj = 0; jj < 3; ++jj) {
                    mu = __vmaxu2(__vmaxu2(mu, v[jj].x), v[jj].y); mu = __vmaxu2(__vmaxu2(mu, v[jj].z), v[jj].w);
                    ms = __vmaxs2(__vmaxs2(ms, v[jj].x), v[jj].y); ms = __vmaxs2(__vmaxs2(ms, v[jj].z), v[jj].w);
                    o[jj * 4 + 0] = hmul2_bf16(v[jj].x, gh[jj * 4 + 0]);
                    o[jj * 4 + 1] = hmul2_bf16(v[jj].y, gh[jj * 4 + 1]);
                    o[jj * 4 + 2] = hmul2_bf16(v[jj].z, gh[jj * 4 + 2]);
                    o[jj * 4 + 3] = hmul2_bf16(v[jj].w, gh[jj * 4 + 3]);
                    if (i < 5) v[jj] = lds128(w2b + (i + 1) * (8 * CH * 2) + g * (CH * 2) + jj * 64 + q * 16);
                }
                __syncwarp();
#pragma unroll
                for (int e = 0; e < 12; ++e) o[e] = bf2_to_h2(o[e]);
#pragma unroll
                for (int jj = 0; jj < 3; ++jj)
                    stsm_x4(w2b + i * (8 * CH * 2) + jj * 512 + lane * 16, o[jj * 4], o[jj * 4 + 1], o[jj * 4 + 2], o[jj * 4 + 3]);
            }
            TL(103);
            mu = __vmaxu2(mu & 0x7fff7fffu, ms);
            return __reduce_max_sync(0xffffffffu, max(mu & 0xffffu, mu >> 16));
        };
        if (warp != 11) asm volatile("bar.sync 2, %0;" ::"n"(NUM_THREADS) : "memory");
        TL(82);
        asm volatile("setmaxnreg.inc.sync.aligned.u32 %0;" ::"n"(RMLP));
        {
            const int box = warp >> 1, cc = lane & 7, k0 = (warp & 1) * 48 + (lane >> 3);
            constexpr uint32_t DN = 0x07800780u;
            TL(3);
            if (warp == 0) {
                sts128(sbase + OFF_ONES + lane * 16, lane < 16 ? 0x3F80u : 0x3F800000u, lane < 16 ? 0x3F80u : 0x3F800000u,
                       lane < 16 ? 0x3F80u : 0x3F800000u, lane < 16 ? 0x3F80u : 0x3F800000u);
            }
            const uint32_t m[4] = {hmul2_bf16(r95.x, DN | 0x80008000u), hmul2_bf16(r95.y, DN | 0x80008000u),
                                   hmul2_bf16(r95.z, DN | 0x80008000u), hmul2_bf16(r95.w, DN | 0x80008000u)};
            const uint32_t tb[4] = {scale2h(bb.x, GELU_A), scale2h(bb.y, GELU_A), scale2h(bb.z, GELU_A), scale2h(bb.w, GELU_A)};
            uint32_t mx = absmax2(absmax2(absmax2(absmax2(0, hmul2_bf16(bb.x, DN)), hmul2_bf16(bb.y, DN)), hmul2_bf16(bb.z, DN)), hmul2_bf16(bb.w, DN));
            uint32_t mg = 0;
#pragma unroll
            for (int jj = 0; jj < 3; ++jj) mg = absmax2(absmax2(absmax2(absmax2(mg, gm[jj].x), gm[jj].y), gm[jj].z), gm[jj].w);
            mg = __reduce_max_sync(0xffffffffu, max(mg & 0xffffu, mg >> 16));
            if (warp == 4 || warp == 5) {
                const uint32_t mb = __reduce_max_sync(0xffffffffu, max(b2v & 0x7fffu, (b2v >> 16) & 0x7fffu));
                if (lane == 0) sts32(sbase + OFF_MAX + 32 + warp * 4, mb);
            }
            const uint32_t wb = sbase + OFF_W1 + box * (CH * NCH * 2);
            const uint32_t a0 = wb + k0 * 128 + ((cc ^ (k0 & 7)) << 4), a1_ = wb + (k0 + 4) * 128 + ((cc ^ ((k0 + 4) & 7)) << 4);
            mbar_wait(bars + 8 * (BAR_W1 + box), 0);
            TL(2);
            uint4 u[2] = {lds128(a0), lds128(a1_)};
#pragma unroll 1
            for (int i = 0; i < 6; ++i) {
                TL(90 + i);
                uint32_t t[2][4];
#pragma unroll
                for (int e = 0; e < 2; ++e) {
                    t[e][0] = hfma2_bf16(u[e].x, DN, m[0]); t[e][1] = hfma2_bf16(u[e].y, DN, m[1]);
                    t[e][2] = hfma2_bf16(u[e].z, DN, m[2]); t[e][3] = hfma2_bf16(u[e].w, DN, m[3]);
                    if (i < 5) u[e] = lds128((e ? a1_ : a0) + (i + 1) * 1024);
#pragma unroll
                    for (int x = 0; x < 4; ++x) {
                        mx = absmax2(mx, t[e][x]);
                        t[e][x] = bf2_to_h2(t[e][x]);
                    }
                }
                sts128(a0 + i * 1024, t[0][0], t[0][1], t[0][2], t[0][3]);
                sts128(a1_ + i * 1024, t[1][0], t[1][1], t[1][2], t[1][3]);
            }
            if (k0 + 44 == 95) sts128(a1_ + 5 * 1024, tb[0], tb[1], tb[2], tb[3]);
            const uint32_t m1w = __reduce_max_sync(0xffffffffu, max(mx & 0xffffu, mx >> 16));
            if (lane == 0) sts32(sbase + OFF_MAX + warp * 4, m1w << 16);
            asm volatile("fence.proxy.async.shared::cta;" ::: "memory");
            __syncwarp();
            if (elect_one()) mbar_arrive(bars + 8 * BAR_W1RDY);
            TL(100);
            if (wg > 0) {
                const uint32_t m2w = transform_w2(0, 0);
                if (lane == 0) sts32(sbase + OFF_MAX + warp * 4, m2w | (m1w << 16));
                asm volatile("fence.proxy.async.shared::cta;" ::: "memory");
                mbar_wait(bars + 8 * BAR_W1RDY, 0);
                asm volatile("bar.sync 1, 256;" ::: "memory");
                const uint32_t mm = lane < 14 ? lds32(sbase + OFF_MAX + lane * 4) : 0;
                const uint32_t m1 = __reduce_max_sync(0xffffffffu, lane < 12 ? mm >> 16 : 0);
                const uint32_t m2 = __reduce_max_sync(0xffffffffu, lane < 12 ? mm & 0xffffu : 0), mb = __reduce_max_sync(0xffffffffu, lane < 12 ? 0 : mm);
                const int e1 = max((int)(m1 >> 7), 1) - 14, eg = (int)(mg >> 7) - 126, ew = (int)(m2 >> 7) - 126;
                const int e2 = ew + eg + 1, eb = (int)(mb >> 7) - 126 + eg;
                int s = min(min(-1 - e1 - e2, 14 - eb), 14 - e2);
                if (s >= 0 && s <= 12 && e2 >= -9 && eg >= -9) s = 0;
                s = min(max(s, -120), min(120, 120 - eg));
                if (s != 0) {
                    if ((warp & 1) == 0 && elect_one()) load_w2((warp >> 1) - 2);
                    transform_w2(s, 1);
                    asm volatile("fence.proxy.async.shared::cta;" ::: "memory");
                }
                if (tid == 128) sts32(sbase + OFF_MAX + 64, (uint32_t)(127 - s) * 0x00800080u);
                __syncwarp();
                if (elect_one()) mbar_arrive(bars + 8 * BAR_W2RDY);
            } else if (DRY != 2 && wr < 2) {
                mbar_wait(bars + 8 * BAR_PRIME, 0);
                if (elect_one()) load_row(4 + wr);
            }
        }
        TL(1);
        const uint64_t descW1 = make_desc(sbase + OFF_W1, CH * NCH * 2, 1024) | (1ull << 62);
        const uint64_t descW2 = make_desc(sbase + OFF_W2, (CH / 8) * 128, 128);
        const uint64_t descS = make_desc(sbase + OFF_ONES, 128, 128);
        uint32_t la = sbase + OFF_A + (wg & 1) * A_BYTES + wr * 16 * A_PITCH + (wr >> 1) * 64 +
                            (uint32_t)(((lane & 7) + ((lane >> 3) & 1) * 8) * A_PITCH + (lane >> 4) * 16);

        uint32_t acc2[24];
        uint32_t h[2][NCH / 4];
        uint32_t a1[6][4];
        uint32_t ps[4], pq[4];
        float st[4];

        auto load_a = [&]() {
#pragma unroll
            for (int kb = 0; kb < 6; ++kb) ldsm_x4(la + kb * 32, a1[kb][0], a1[kb][1], a1[kb][2], a1[kb][3]);
        };
        auto partial_a = [&](int i) {
            {
                ps[i] = hadd2_bf16(hadd2_bf16(hadd2_bf16(a1[0][i], a1[1][i]), hadd2_bf16(a1[2][i], a1[3][i])), hadd2_bf16(a1[4][i], a1[5][i]));
                pq[i] = hmul2_bf16(a1[0][i], a1[0][i]);
#pragma unroll
                for (int kb = 1; kb < 6; ++kb) pq[i] = hfma2_bf16(a1[kb][i], a1[kb][i], pq[i]);
                asm volatile("" : "+r"(ps[i]), "+r"(pq[i]));
            }
        };
        auto reduce_a = [&]() {
            wgmma_stat_first(st, ps, descS);
            wgmma_stat_acc(st, pq, descS + 16);
        };
        uint32_t sel95 = q == 3 ? 0x7610 : 0x3210;
        asm volatile("" : "+r"(sel95));
        auto norm_a = [&]() {
            constexpr float K = GELU_A * 0x1p-112f, SQ = 9.797958971132712f;
            float m0 = st[0] * (-1.f / CH), m1 = st[2] * (-1.f / CH);
            float r0, r1;
            asm("rsqrt.approx.ftz.f32 %0, %1;" : "=f"(r0) : "f"(fmaxf(fmaf(m0, st[0], st[1]), 0.f) + CH * 1e-5f));
            asm("rsqrt.approx.ftz.f32 %0, %1;" : "=f"(r1) : "f"(fmaxf(fmaf(m1, st[2], st[3]), 0.f) + CH * 1e-5f));
            const uint32_t rp = pack_bf16(r0 * (K * SQ), r1 * (K * SQ));
            const float o0 = m0 * bf_lo(rp), o1 = m1 * bf_hi(rp);
            const uint32_t op = pack_bf16(o0, o1);
            const bool easy = (fmaxf(fabsf(o0), fabsf(o1)) < 0.5f * K) & (fminf(r0, r1) > 0x1p-12f);
            if (__all_sync(0xffffffffu, easy)) {
#pragma unroll
                for (int kb = 0; kb < 6; ++kb)
#pragma unroll
                    for (int i = 0; i < 4; ++i) {
                        uint32_t y;
                        if (i & 1)
                            asm("{\n\t.reg .b16 a, b, c, d;\n\t.reg .b32 r, o;\n\tmov.b32 {a, b}, %2;\n\tmov.b32 {c, d}, %3;\n\t"
                                "mov.b32 r, {b, b};\n\tmov.b32 o, {d, d};\n\tfma.rn.bf16x2 %0, %1, r, o;\n\t}" : "=r"(y) : "r"(a1[kb][i]), "r"(rp), "r"(op));
                        else
                            asm("{\n\t.reg .b16 a, b, c, d;\n\t.reg .b32 r, o;\n\tmov.b32 {a, b}, %2;\n\tmov.b32 {c, d}, %3;\n\t"
                                "mov.b32 r, {a, a};\n\tmov.b32 o, {c, c};\n\tfma.rn.bf16x2 %0, %1, r, o;\n\t}" : "=r"(y) : "r"(a1[kb][i]), "r"(rp), "r"(op));
                        a1[kb][i] = bf2_to_h2(y);
                    }
            } else {
                float s0[2] = {0.f, 0.f}, s1[2] = {0.f, 0.f}, v0[2] = {0.f, 0.f}, v1[2] = {0.f, 0.f};
#pragma unroll
                for (int kb = 0; kb < 6; ++kb)
#pragma unroll
                    for (int i = 0; i < 2; ++i) {
                        float a = bf_lo(a1[kb][2 * i]), b = bf_hi(a1[kb][2 * i]);
                        s0[0] += a; v0[0] = fmaf(a, a, v0[0]); s0[1] += b; v0[1] = fmaf(b, b, v0[1]);
                        a = bf_lo(a1[kb][2 * i + 1]); b = bf_hi(a1[kb][2 * i + 1]);
                        s1[0] += a; v1[0] = fmaf(a, a, v1[0]); s1[1] += b; v1[1] = fmaf(b, b, v1[1]);
                    }
                float sa = s0[0] + s0[1], sb = s1[0] + s1[1], va = v0[0] + v0[1], vb = v1[0] + v1[1];
                sa += __shfl_xor_sync(0xffffffffu, sa, 1); sb += __shfl_xor_sync(0xffffffffu, sb, 1);
                va += __shfl_xor_sync(0xffffffffu, va, 1); vb += __shfl_xor_sync(0xffffffffu, vb, 1);
                sa += __shfl_xor_sync(0xffffffffu, sa, 2); sb += __shfl_xor_sync(0xffffffffu, sb, 2);
                va += __shfl_xor_sync(0xffffffffu, va, 2); vb += __shfl_xor_sync(0xffffffffu, vb, 2);
                m0 = sa * (1.f / CH); m1 = sb * (1.f / CH);
                asm("rsqrt.approx.ftz.f32 %0, %1;" : "=f"(r0) : "f"(fmaxf(fmaf(-m0, m0, va * (1.f / CH)), 0.f) + 1e-5f));
                asm("rsqrt.approx.ftz.f32 %0, %1;" : "=f"(r1) : "f"(fmaxf(fmaf(-m1, m1, vb * (1.f / CH)), 0.f) + 1e-5f));
                r0 *= GELU_A; r1 *= GELU_A;
                const float p0 = -m0 * r0, p1 = -m1 * r1;
#pragma unroll
                for (int kb = 0; kb < 6; ++kb)
#pragma unroll
                    for (int i = 0; i < 4; ++i) {
                        const float r = (i & 1) ? r1 : r0, o = (i & 1) ? p1 : p0;
                        a1[kb][i] = pack_f16(fmaf(bf_lo(a1[kb][i]), r, o), fmaf(bf_hi(a1[kb][i]), r, o));
                    }
            }
            a1[5][2] = __byte_perm(a1[5][2], 0x3C000000u, sel95);
            a1[5][3] = __byte_perm(a1[5][3], 0x3C000000u, sel95);
        };
        auto gemm1 = [&](uint32_t (&d)[NCH / 4], int c) {
            WH<NCH>::first(d, a1[0][0], a1[0][1], a1[0][2], a1[0][3], descW1 + (uint64_t)(c * 768));
#pragma unroll
            for (int kk = 1; kk < 6; ++kk)
                WH<NCH>::acc(d, a1[kk][0], a1[kk][1], a1[kk][2], a1[kk][3], descW1 + (uint64_t)(c * 768 + kk * 128));
        };
        uint32_t b2a = sbase + OFF_B2I + q * 16;
        asm volatile("" : "+r"(b2a));
        auto init_acc = [&]() {
#pragma unroll
            for (int m = 0; m < 6; ++m) {
                const uint4 v = lds128(b2a + m * 64);
                acc2[4 * m] = v.x; acc2[4 * m + 1] = v.y; acc2[4 * m + 2] = v.z; acc2[4 * m + 3] = v.w;
            }
        };

        mbar_wait(bars + 8 * BAR_W1RDY, 0);
        static_assert((OFF_BAR + 8 * BAR_A_EMPTY) % 16 == 0, "xor toggle");
        const uint32_t nbar = bars + 8 * (BAR_DONE + wg), tbar = bars + 8 * (BAR_DONE + (wg + 1) % NMLP);
        uint32_t ebar = bars + 8 * (BAR_A_EMPTY + (wg & 1)), nph = 0;
        const uint32_t lsum = 2 * la + ((wg & 1) ? -A_BYTES : A_BYTES);
#pragma unroll 1
        for (int rep = (DRY && wg == 0) ? 0 : 1; rep < 2; ++rep) {
        if (rep) mbar_wait(nbar, 0);
        load_a();
        TL(104);
#pragma unroll
        for (int i = 0; i < 4; ++i) partial_a(i);
        wg_fence();
        reduce_a();
        wg_commit();
        wg_wait<0>();
        fence_regs(st);
        norm_a();
        TL(105);
        __syncwarp();
        if (rep && elect_one()) {
            mbar_arrive(ebar);
            mbar_arrive(tbar);
        }
        wg_fence();
        gemm1(h[0], 0);
        wg_commit();
        wg_wait<0>();
        if (DRY == 2 && !rep && wr < 2) {
            mbar_wait(bars + 8 * BAR_PRIME, 0);
            if (elect_one()) load_row(4 + wr);
        }
        }
        mbar_wait(bars + 8 * BAR_W2RDY, 0);
        const uint32_t oscale = lds32(sbase + OFF_MAX + 64);
        wg_wait<0>();
        uint32_t y[24];
#pragma unroll
        for (int i = 0; i < 24; ++i) y[i] = 0;
        auto flush_y = [&](__nv_bfloat16* p) {
#pragma unroll
            for (int jj = 0; jj < 3; ++jj)
#pragma unroll
                for (int hrow = 0; hrow < 2; ++hrow)
                    red_add_bf16x8(p + hrow * 8 * CH + jj * 32, y[jj * 8 + hrow], y[jj * 8 + hrow + 2], y[jj * 8 + hrow + 4], y[jj * 8 + hrow + 6]);
        };
        __nv_bfloat16* optr = out + ((ys + dir * (wg + 1 - (UNC ? 0 : NMLP))) * IMG_W + strip * STRIP_W + wr * 16 + g) * CH + q * 8;
        auto store_y = [&](int i, uint4 xv) {
            const int jj = i >> 1, hrow = i & 1;
            stg128(optr + hrow * 8 * CH + jj * 32, hadd2_bf16(xv.x, y[jj * 8 + hrow]), hadd2_bf16(xv.y, y[jj * 8 + hrow + 2]),
                   hadd2_bf16(xv.z, y[jj * 8 + hrow + 4]), hadd2_bf16(xv.w, y[jj * 8 + hrow + 6]));
        };
#pragma unroll 1
        for (int t = wg;; t += NMLP) {
            TL(4 + 2 * (t / NMLP));
            bool ready = true;
            const uint64_t rpol = (t != wg && t < EFT) ? policy_evict_first() : policy_evict_normal();
            SCHED_FENCE();
            constexpr int P = NCH / 4, NP = HID / 4;
            uint32_t zz[3];
            uint4 xq[6];
            uint16_t t0[LB], t1[LB];
#pragma unroll
            for (int G = 0; G <= NP + LAG; ++G) {
                const int ca = G / P;
                if (G == NP - P - TESTPOS) ready = mbar_test(nbar, nph) || (MORE && t + NMLP >= ROWS_PER_CTA);
                if (G == NP - P && !ready) mbar_wait(nbar, nph);
                if (G % P == 0 && ca >= 1 && G < NP) { wg_wait<G2INFL>(); fence_regs(h[ca & 1]); }
                if (G == NP - P) load_a();
                if (G == STATPOS) {
                    wg_fence();
                    reduce_a();
                    wg_commit();
                }
                {
                    bool fenced = false;
                    const int pa = ca == 0 ? 1 : G1PA, pb = ca == 0 ? (G1PB == G1PA ? 1 : 3) : G1PB;
                    if (ca + 1 < NCHUNK && (G % P == pa || G % P == pb)) {
                        if (ca > 0 && G % P == pa) wg_wait<0>();
                        wg_fence();
                        fenced = true;
                        uint32_t (&d)[NCH / 4] = h[(ca + 1) & 1];
#pragma unroll
                        for (int kk = 0; kk < 6; ++kk) {
                            if (G % P != (kk < G1N ? pa : pb)) continue;
                            if (kk == 0) WH<NCH>::first(d, a1[0][0], a1[0][1], a1[0][2], a1[0][3], descW1 + (uint64_t)((ca + 1) * 768));
                            else WH<NCH>::acc(d, a1[kk][0], a1[kk][1], a1[kk][2], a1[kk][3], descW1 + (uint64_t)((ca + 1) * 768 + kk * 128));
                        }
                        if (G % P == pb) wg_commit();
                    }
                    bool any = false;
#pragma unroll
                    for (int kk = 0; kk < NCH / 16; ++kk) {
                        const int pos = kk == 0 ? G2P0 : kk == 1 ? G2P1 : kk == 2 ? G2P2 : G2P3;
                        if (G < pos || (G - pos) % P != 0 || (G - pos) / P >= NCHUNK) continue;
                        const int c = (G - pos) / P;
                        if (!any) fence_regs(h[c & 1]);
                        if (!fenced) wg_fence();
                        fenced = any = true;
                        WH<96>::acc(acc2, h[c & 1][kk * 4], h[c & 1][kk * 4 + 1], h[c & 1][kk * 4 + 2], h[c & 1][kk * 4 + 3],
                                    descW2 + (uint64_t)(((c * (NCH / 8) + 2 * kk) * (CH / 8)) * 8));
                    }
                    if (any) wg_commit();
                }
                if (G == INITPOS) init_acc();
                if (G == RELPOS) {
                    __syncwarp();
                    if (elect_one()) mbar_arrive(ebar);
                }
                if (!RESID && G >= REDPOS && G < REDPOS + 6 * REDSTEP && (G - REDPOS) % REDSTEP == 0) {
                    const int jj = (G - REDPOS) / REDSTEP / 2, hrow = (G - REDPOS) / REDSTEP % 2;
                    red_add_bf16x8_pol(optr + hrow * 8 * CH + jj * 32, y[jj * 8 + hrow], y[jj * 8 + hrow + 2], y[jj * 8 + hrow + 4], y[jj * 8 + hrow + 6], rpol);
                }
                if (G == 4 * P + 4) {
                    static_assert(NMLP & 1, "slot alternates");
                    asm volatile("sub.u32 %0, %1, %0;" : "+r"(la) : "r"(lsum));
                    ebar ^= 8;
                    nph ^= 1;
                    asm volatile("add.u64 %0, %0, %1;" : "+l"(optr) : "l"((UNC && t == wg) ? 0ll : (long long)dir * (NMLP * IMG_W * CH * 2)));
                }
                if (G >= STATPOS - 4 && G < STATPOS) partial_a(G - (STATPOS - 4));
                int e = G - LAG;
                if (e >= 0 && e < NP) {
                    uint32_t& v = h[(e / P) & 1][e % P];
                    uint32_t o;
                    asm volatile("{\n\t.reg .b32 t;\n\tmov.b32 t, {%2, %3};\n\tfma.rn.f16x2 %0, %1, t, %1;\n\t}"
                                 : "=r"(o) : "r"(v), "h"(t0[e % LB]), "h"(t1[e % LB]));
                    v = o;
                }
                e = G - 1;
                if (e >= 0 && e < NP)
                    asm volatile("{\n\t.reg .b16 l, h;\n\tmov.b32 {l, h}, %2;\n\ttanh.approx.f16 %0, l;\n\ttanh.approx.f16 %1, h;\n\t}"
                                 : "=h"(t0[e % LB]), "=h"(t1[e % LB]) : "r"(zz[e & 1]));
                if (G < NP)
                    asm volatile("{\n\t.reg .b32 p;\n\tfma.rn.f16x2 p, %1, %1, %2;\n\tmul.rn.f16x2 %0, %1, p;\n\t}"
                                 : "=r"(zz[G & 1]) : "r"(h[ca & 1][G % P]), "r"(0x40D940D9u));
                SCHED_FENCE();
            }
            if (t + NMLP >= ROWS_PER_CTA) break;
            wg_wait<1>();
            fence_regs(st);
            norm_a();
            if (TOKB == 0 && elect_one()) mbar_arrive(tbar);
            wg_fence();
            gemm1(h[0], 0);
            wg_commit();
            if (TOKB == 1 && elect_one()) mbar_arrive(tbar);
            SCHED_FENCE();
            wg_wait<1>();
            fence_regs(acc2);
            TL(5 + 2 * (t / NMLP));
#pragma unroll
            for (int i = 0; i < 24; ++i) {
                if (TOKB >= 2 && i == (TOKB - 1) * 8) { fence_regs(y); SCHED_FENCE(); if (elect_one()) mbar_arrive(tbar); SCHED_FENCE(); }
                y[i] = h2_to_bf2(acc2[i]);
            }
            if (TOKB == 4 && elect_one()) mbar_arrive(tbar);
            if (oscale != 0x3F803F80u) {
#pragma unroll
                for (int i = 0; i < 24; ++i) y[i] = hmul2_bf16(y[i], oscale);
            }
            wg_wait<0>();
        }
        wg_wait<0>();
        fence_regs(acc2);
#pragma unroll
        for (int i = 0; i < 24; ++i) y[i] = hmul2_bf16(h2_to_bf2(acc2[i]), oscale);
        flush_y(optr);
        TL(5 + 2 * 10);
        CK_END();
    }
}

typedef CUresult (*PFN_encodeTiled)(CUtensorMap*, CUtensorMapDataType, cuuint32_t, void*, const cuuint64_t*,
                                    const cuuint64_t*, const cuuint32_t*, const cuuint32_t*, CUtensorMapInterleave,
                                    CUtensorMapSwizzle, CUtensorMapL2promotion, CUtensorMapFloatOOBfill);

}

extern "C" void kernel_launch(void* const* d_in, const int* in_sizes, int n_in, void* d_out, int out_size) {
    const __nv_bfloat16* x = (const __nv_bfloat16*)d_in[0];
    const __nv_bfloat16* dw = (const __nv_bfloat16*)d_in[1];
    const __nv_bfloat16* w1 = (const __nv_bfloat16*)d_in[2];
    const __nv_bfloat16* b1 = (const __nv_bfloat16*)d_in[3];
    const __nv_bfloat16* w2 = (const __nv_bfloat16*)d_in[4];
    const __nv_bfloat16* b2 = (const __nv_bfloat16*)d_in[5];
    const __nv_bfloat16* gamma = (const __nv_bfloat16*)d_in[6];
    __nv_bfloat16* out = (__nv_bfloat16*)d_out;

    static PFN_encodeTiled encode = nullptr;
    if (!encode) {
        void* fn = nullptr;
        cudaDriverEntryPointQueryResult qres;
        cudaGetDriverEntryPoint("cuTensorMapEncodeTiled", &fn, cudaEnableDefault, &qres);
        encode = (PFN_encodeTiled)fn;
        cudaFuncSetAttribute(convnext_fused_kernel, cudaFuncAttributeMaxDynamicSharedMemorySize, SMEM_BYTES);
    }
    CUtensorMap xmap, w1map;
    cuuint64_t gdim[3] = {CH, IMG_W, IMG_H};
    cuuint64_t gstr[2] = {CH * 2, (cuuint64_t)IMG_W * CH * 2};
    cuuint32_t box[3] = {CH, HALF_W, 1};
    cuuint32_t estr[3] = {1, 1, 1};
    encode(&xmap, CU_TENSOR_MAP_DATA_TYPE_BFLOAT16, 3, (void*)x, gdim, gstr, box, estr, CU_TENSOR_MAP_INTERLEAVE_NONE,
           CU_TENSOR_MAP_SWIZZLE_NONE, XPROMO, CU_TENSOR_MAP_FLOAT_OOB_FILL_NONE);
    cuuint64_t wdim[2] = {HID, CH};
    cuuint64_t wstr[1] = {HID * 2};
    cuuint32_t wbox[2] = {NCH, CH};
    encode(&w1map, CU_TENSOR_MAP_DATA_TYPE_BFLOAT16, 2, (void*)w1, wdim, wstr, wbox, estr, CU_TENSOR_MAP_INTERLEAVE_NONE,
           CU_TENSOR_MAP_SWIZZLE_128B, CU_TENSOR_MAP_L2_PROMOTION_L2_256B, CU_TENSOR_MAP_FLOAT_OOB_FILL_NONE);

    convnext_fused_kernel<<<NUM_CTAS, NUM_THREADS, SMEM_BYTES>>>(xmap, w1map, dw, w1, b1, w2, b2, gamma, out, (long long)((const char*)x - (const char*)out), 0u);
}
```

```cpp
#include <cuda_runtime.h>
#include <cuda_bf16.h>
#include <cuda.h>
#include <stdint.h>

namespace {

constexpr int IMG_H = 512, IMG_W = 512, CH = 96, HID = 384;
constexpr int STRIP_W = 64;
constexpr int NUM_STRIPS = IMG_W / STRIP_W;
constexpr int ROWS_PER_CTA = 32;
constexpr int NUM_CTAS = NUM_STRIPS * (IMG_H / ROWS_PER_CTA);
constexpr int HALF_W = STRIP_W / 2 + 3;
constexpr int HALF_BYTES = HALF_W * CH * 2;
constexpr int HALF_BOX = ((HALF_BYTES + 127) / 128) * 128;
constexpr int HALF_OFF = HALF_BOX + CH * 2;
constexpr int ROW_BYTES = 2 * HALF_BOX;
constexpr int NROW = 4;
constexpr int NA = 2;
constexpr int A_PITCH = CH * 2 + 16;
constexpr int A_HALF = 32 * A_PITCH + 64;
constexpr int A_BYTES = ((A_HALF + 32 * A_PITCH + 127) / 128) * 128;
constexpr int NCH = 64;
constexpr int NCHUNK = HID / NCH;
constexpr int NMLP = 3;

#define G1PA_ 7
#define G1PB_ 10
#define G2PA_ 13
#define RELPOS_ 94
#define REDPOS_ 8
#define REDSTEP_ 6
constexpr int LAG = 3;
constexpr int G1PA = G1PA_, G1PB = G1PB_;
constexpr int G2PA = G2PA_, G2PB = 16 + LAG;
constexpr int INITPOS = 2, REDPOS = REDPOS_, REDSTEP = REDSTEP_, TESTPOS = 76, RELPOS = RELPOS_;
constexpr int STATPOS = 80 + G2PA;
static_assert(G1PA < G1PB && G1PB < G2PA && G2PA >= 8 + LAG && G2PA < 16 && RELPOS >= STATPOS, "schedule");

constexpr int OFF_W1 = 0;
constexpr int OFF_W2 = OFF_W1 + CH * HID * 2;
constexpr int OFF_ROW = OFF_W2 + CH * HID * 2;
constexpr int OFF_A = OFF_ROW + NROW * ROW_BYTES;
constexpr int OFF_SEL = OFF_A + NA * A_BYTES;
constexpr int OFF_B2I = OFF_SEL + 256;
constexpr int OFF_MAX = OFF_B2I + 384;
constexpr int OFF_DW = OFF_MAX + 128;
constexpr int OFF_BAR = OFF_DW + 9 * CH * 2;
constexpr int BAR_ROW_FULL = 0, BAR_DONE = NROW, BAR_PRIME = BAR_DONE + NMLP, BAR_FREE = BAR_PRIME + 1, BAR_A_EMPTY = BAR_FREE + 2;
constexpr int BAR_W1 = BAR_A_EMPTY + NA, BAR_W2 = BAR_W1 + NCHUNK, BAR_DW = BAR_W2 + 4;
constexpr int BAR_W1RDY = BAR_DW + 1, BAR_W2RDY = BAR_W1RDY + 1;
constexpr int NUM_BARS = BAR_W2RDY + 1;
constexpr int SMEM_BYTES = OFF_BAR + NUM_BARS * 8;
static_assert(SMEM_BYTES <= 232448, "smem");
static_assert(HALF_OFF % 128 == 64 && OFF_ROW % 128 == 0 && OFF_SEL % 128 == 0, "bank layout");

constexpr int NUM_THREADS = 128 * (NMLP + 1);

constexpr float GELU_A = 0.7978845608028654f / 2.423828125f;
constexpr float GELU_INV2A = 0.5f / GELU_A;

__device__ __forceinline__ uint32_t smem_u32(const void* p) { return (uint32_t)__cvta_generic_to_shared(p); }

__device__ __forceinline__ void mbar_init(uint32_t bar, uint32_t count) {
    asm volatile("mbarrier.init.shared::cta.b64 [%0], %1;" ::"r"(bar), "r"(count) : "memory");
}
__device__ __forceinline__ void mbar_expect_tx(uint32_t bar, uint32_t bytes) {
    asm volatile("mbarrier.arrive.expect_tx.shared::cta.b64 _, [%0], %1;" ::"r"(bar), "r"(bytes) : "memory");
}
__device__ __forceinline__ void mbar_arrive(uint32_t bar) {
    asm volatile("mbarrier.arrive.shared::cta.b64 _, [%0];" ::"r"(bar) : "memory");
}
__device__ __forceinline__ bool mbar_test(uint32_t bar, uint32_t parity) {
    uint32_t done;
    asm volatile(
        "{\n\t.reg .pred p;\n\t"
        "mbarrier.test_wait.parity.shared::cta.b64 p, [%1], %2;\n\t"
        "selp.u32 %0, 1, 0, p;\n\t}"
        : "=r"(done) : "r"(bar), "r"(parity) : "memory");
    return done != 0;
}
__device__ __forceinline__ void mbar_wait(uint32_t bar, uint32_t parity) {
    for (int it = 0; it < (1 << 20); ++it) {
        uint32_t done;
        asm volatile(
            "{\n\t.reg .pred p;\n\t"
            "mbarrier.try_wait.parity.shared::cta.b64 p, [%1], %2;\n\t"
            "selp.u32 %0, 1, 0, p;\n\t}"
            : "=r"(done) : "r"(bar), "r"(parity) : "memory");
        if (done) break;
    }
}
__device__ __forceinline__ uint64_t policy_evict_first() {
    uint64_t p;
    asm("createpolicy.fractional.L2::evict_first.b64 %0, 1.0;" : "=l"(p));
    return p;
}
__device__ __forceinline__ uint64_t policy_evict_normal() {
    uint64_t p;
    asm("createpolicy.fractional.L2::evict_normal.b64 %0, 1.0;" : "=l"(p));
    return p;
}
__device__ __forceinline__ void tma_load_3d(uint32_t dst, const CUtensorMap* map, uint32_t bar, int c0, int c1, int c2) {
    asm volatile(
        "cp.async.bulk.tensor.3d.shared::cluster.global.mbarrier::complete_tx::bytes.L2::cache_hint [%0], [%1, {%3, %4, %5}], [%2], %6;"
        ::"r"(dst), "l"(reinterpret_cast<uint64_t>(map)), "r"(bar), "r"(c0), "r"(c1), "r"(c2), "l"(policy_evict_first()) : "memory");
}
__device__ __forceinline__ void tma_load_2d(uint32_t dst, const CUtensorMap* map, uint32_t bar, int c0, int c1) {
    asm volatile(
        "cp.async.bulk.tensor.2d.shared::cluster.global.mbarrier::complete_tx::bytes [%0], [%1, {%3, %4}], [%2];"
        ::"r"(dst), "l"(reinterpret_cast<uint64_t>(map)), "r"(bar), "r"(c0), "r"(c1) : "memory");
}
__device__ __forceinline__ bool elect_one() {
    uint32_t p;
    asm volatile("{\n\t.reg .pred p;\n\telect.sync _|p, 0xffffffff;\n\tselp.u32 %0, 1, 0, p;\n\t}" : "=r"(p));
    return p != 0;
}
__device__ __forceinline__ void bulk_load(uint32_t dst, const void* src, uint32_t bytes, uint32_t bar) {
    asm volatile("cp.async.bulk.shared::cluster.global.mbarrier::complete_tx::bytes [%0], [%1], %2, [%3];"
                 ::"r"(dst), "l"(src), "r"(bytes), "r"(bar) : "memory");
}
__device__ __forceinline__ void bulk_store(void* dst, uint32_t src, uint32_t bytes) {
    asm volatile("cp.async.bulk.global.shared::cta.bulk_group [%0], [%1], %2;" ::"l"(dst), "r"(src), "r"(bytes) : "memory");
}
__device__ __forceinline__ void bulk_commit() { asm volatile("cp.async.bulk.commit_group;" ::: "memory"); }
template <int N> __device__ __forceinline__ void bulk_wait_read() {
    asm volatile("cp.async.bulk.wait_group.read %0;" ::"n"(N) : "memory");
}
template <int N> __device__ __forceinline__ void bulk_wait() {
    asm volatile("cp.async.bulk.wait_group %0;" ::"n"(N) : "memory");
}
__device__ __forceinline__ void ldsm_x4(uint32_t addr, uint32_t& r0, uint32_t& r1, uint32_t& r2, uint32_t& r3) {
    asm volatile("ldmatrix.sync.aligned.m8n8.x4.shared.b16 {%0,%1,%2,%3}, [%4];"
                 : "=r"(r0), "=r"(r1), "=r"(r2), "=r"(r3) : "r"(addr) : "memory");
}
__device__ __forceinline__ void ldsm_x2(uint32_t addr, uint32_t& r0, uint32_t& r1) {
    asm volatile("ldmatrix.sync.aligned.m8n8.x2.shared.b16 {%0,%1}, [%2];" : "=r"(r0), "=r"(r1) : "r"(addr) : "memory");
}
__device__ __forceinline__ void stsm_x4(uint32_t addr, uint32_t r0, uint32_t r1, uint32_t r2, uint32_t r3) {
    asm volatile("stmatrix.sync.aligned.m8n8.x4.shared.b16 [%0], {%1,%2,%3,%4};"
                 ::"r"(addr), "r"(r0), "r"(r1), "r"(r2), "r"(r3) : "memory");
}
__device__ __forceinline__ uint4 lds128(uint32_t addr) {
    uint4 v;
    asm volatile("ld.shared.v4.u32 {%0,%1,%2,%3}, [%4];" : "=r"(v.x), "=r"(v.y), "=r"(v.z), "=r"(v.w) : "r"(addr) : "memory");
    return v;
}
__device__ __forceinline__ uint32_t lds32(uint32_t addr) {
    uint32_t a;
    asm volatile("ld.shared.u32 %0, [%1];" : "=r"(a) : "r"(addr) : "memory");
    return a;
}
__device__ __forceinline__ void sts32(uint32_t addr, uint32_t a) {
    asm volatile("st.shared.u32 [%0], %1;" ::"r"(addr), "r"(a) : "memory");
}
__device__ __forceinline__ void sts128(uint32_t addr, uint32_t a, uint32_t b, uint32_t c, uint32_t d) {
    asm volatile("st.shared.v4.u32 [%0], {%1,%2,%3,%4};" ::"r"(addr), "r"(a), "r"(b), "r"(c), "r"(d) : "memory");
}
__device__ __forceinline__ uint32_t hfma2_bf16(uint32_t a, uint32_t b, uint32_t c) {
    uint32_t d;
    asm("fma.rn.bf16x2 %0, %1, %2, %3;" : "=r"(d) : "r"(a), "r"(b), "r"(c));
    return d;
}
template <bool HI> __device__ __forceinline__ uint32_t hfma2_bf16_bcast(uint32_t a, uint32_t b, uint32_t c) {
    uint32_t d;
    if (HI)
        asm("{\n\t.reg .b16 a, b, c, d;\n\t.reg .b32 r, o;\n\tmov.b32 {a, b}, %2;\n\tmov.b32 {c, d}, %3;\n\t"
            "mov.b32 r, {b, b};\n\tmov.b32 o, {d, d};\n\tfma.rn.bf16x2 %0, %1, r, o;\n\t}" : "=r"(d) : "r"(a), "r"(b), "r"(c));
    else
        asm("{\n\t.reg .b16 a, b, c, d;\n\t.reg .b32 r, o;\n\tmov.b32 {a, b}, %2;\n\tmov.b32 {c, d}, %3;\n\t"
            "mov.b32 r, {a, a};\n\tmov.b32 o, {c, c};\n\tfma.rn.bf16x2 %0, %1, r, o;\n\t}" : "=r"(d) : "r"(a), "r"(b), "r"(c));
    return d;
}
__device__ __forceinline__ uint32_t hmul2_bf16(uint32_t a, uint32_t b) {
    uint32_t d;
    asm("mul.rn.bf16x2 %0, %1, %2;" : "=r"(d) : "r"(a), "r"(b));
    return d;
}
__device__ __forceinline__ uint32_t hadd2_bf16(uint32_t a, uint32_t b) {
    uint32_t d;
    asm("add.rn.bf16x2 %0, %1, %2;" : "=r"(d) : "r"(a), "r"(b));
    return d;
}
__device__ __forceinline__ float bf_lo(uint32_t v) { return __uint_as_float(v << 16); }
__device__ __forceinline__ float bf_hi(uint32_t v) { return __uint_as_float(v & 0xffff0000u); }
__device__ __forceinline__ uint32_t pack_bf16(float lo, float hi) {
    uint32_t d;
    asm("cvt.rn.bf16x2.f32 %0, %1, %2;" : "=r"(d) : "f"(hi), "f"(lo));
    return d;
}
__device__ __forceinline__ uint32_t pack_f16(float lo, float hi) {
    uint32_t d;
    asm("cvt.rn.f16x2.f32 %0, %1, %2;" : "=r"(d) : "f"(hi), "f"(lo));
    return d;
}
__device__ __forceinline__ uint32_t scale2h(uint32_t v, float s) {
    return pack_f16(bf_lo(v) * s, bf_hi(v) * s);
}
__device__ __forceinline__ uint32_t h2_to_bf2(uint32_t v) {
    uint32_t d;
    asm("{\n\t.reg .b16 l, h;\n\t.reg .f32 a, b;\n\tmov.b32 {l, h}, %1;\n\tcvt.f32.f16 a, l;\n\tcvt.f32.f16 b, h;\n\t"
        "cvt.rn.bf16x2.f32 %0, b, a;\n\t}" : "=r"(d) : "r"(v));
    return d;
}
__device__ __forceinline__ uint32_t bf2_to_h2(uint32_t y) { return (y & 0x7fff7fffu) * 7u + y; }
__device__ __forceinline__ uint32_t absmax2(uint32_t m, uint32_t v) { return __vmaxu2(m, v & 0x7fff7fffu); }
__device__ __forceinline__ void red_add_bf16x8(void* p, uint32_t a, uint32_t b, uint32_t c, uint32_t d, uint64_t pol) {
    asm volatile("red.global.add.noftz.L2::cache_hint.v4.bf16x2 [%0], {%1,%2,%3,%4}, %5;"
                 ::"l"(p), "r"(a), "r"(b), "r"(c), "r"(d), "l"(pol) : "memory");
}
__device__ __forceinline__ void wg_fence() { asm volatile("wgmma.fence.sync.aligned;" ::: "memory"); }
__device__ __forceinline__ void wg_commit() { asm volatile("wgmma.commit_group.sync.aligned;" ::: "memory"); }
template <int N> __device__ __forceinline__ void wg_wait() {
    asm volatile("wgmma.wait_group.sync.aligned %0;" ::"n"(N) : "memory");
}
template <int N> __device__ __forceinline__ void fence_regs(float (&d)[N]) {
#pragma unroll
    for (int i = 0; i < N; ++i) asm volatile("" : "+f"(d[i])::"memory");
}
template <int N> __device__ __forceinline__ void fence_regs(uint32_t (&d)[N]) {
#pragma unroll
    for (int i = 0; i < N; ++i) asm volatile("" : "+r"(d[i])::"memory");
}

template <int N> struct WH;
template <> struct WH<64> {
    static __device__ __forceinline__ void acc(uint32_t* d, uint32_t a0, uint32_t a1, uint32_t a2, uint32_t a3, uint64_t desc) {
        asm volatile("wgmma.mma_async.sync.aligned.m64n64k16.f16.f16.f16 {%0,%1,%2,%3,%4,%5,%6,%7,%8,%9,%10,%11,%12,%13,%14,%15}, "
                     "{%16,%17,%18,%19}, %20, 1, 1, 1, 1;"
                     : "+r"(d[0]), "+r"(d[1]), "+r"(d[2]), "+r"(d[3]), "+r"(d[4]), "+r"(d[5]), "+r"(d[6]), "+r"(d[7]), "+r"(d[8]), "+r"(d[9]), "+r"(d[10]), "+r"(d[11]), "+r"(d[12]), "+r"(d[13]), "+r"(d[14]), "+r"(d[15])
                     : "r"(a0), "r"(a1), "r"(a2), "r"(a3), "l"(desc) : "memory");
    }
    static __device__ __forceinline__ void first(uint32_t* d, uint32_t a0, uint32_t a1, uint32_t a2, uint32_t a3, uint64_t desc) {
        asm volatile("wgmma.mma_async.sync.aligned.m64n64k16.f16.f16.f16 {%0,%1,%2,%3,%4,%5,%6,%7,%8,%9,%10,%11,%12,%13,%14,%15}, "
                     "{%16,%17,%18,%19}, %20, 0, 1, 1, 1;"
                     : "=r"(d[0]), "=r"(d[1]), "=r"(d[2]), "=r"(d[3]), "=r"(d[4]), "=r"(d[5]), "=r"(d[6]), "=r"(d[7]), "=r"(d[8]), "=r"(d[9]), "=r"(d[10]), "=r"(d[11]), "=r"(d[12]), "=r"(d[13]), "=r"(d[14]), "=r"(d[15])
                     : "r"(a0), "r"(a1), "r"(a2), "r"(a3), "l"(desc) : "memory");
    }
};
template <> struct WH<96> {
    static __device__ __forceinline__ void acc(uint32_t* d, uint32_t a0, uint32_t a1, uint32_t a2, uint32_t a3, uint64_t desc) {
        asm volatile("wgmma.mma_async.sync.aligned.m64n96k16.f16.f16.f16 {%0,%1,%2,%3,%4,%5,%6,%7,%8,%9,%10,%11,%12,%13,%14,%15,%16,%17,%18,%19,%20,%21,%22,%23}, "
                     "{%24,%25,%26,%27}, %28, 1, 1, 1, 1;"
                     : "+r"(d[0]), "+r"(d[1]), "+r"(d[2]), "+r"(d[3]), "+r"(d[4]), "+r"(d[5]), "+r"(d[6]), "+r"(d[7]), "+r"(d[8]), "+r"(d[9]), "+r"(d[10]), "+r"(d[11]), "+r"(d[12]), "+r"(d[13]), "+r"(d[14]), "+r"(d[15]), "+r"(d[16]), "+r"(d[17]), "+r"(d[18]), "+r"(d[19]), "+r"(d[20]), "+r"(d[21]), "+r"(d[22]), "+r"(d[23])
                     : "r"(a0), "r"(a1), "r"(a2), "r"(a3), "l"(desc) : "memory");
    }
    static __device__ __forceinline__ void first(uint32_t* d, uint32_t a0, uint32_t a1, uint32_t a2, uint32_t a3, uint64_t desc) {
        asm volatile("wgmma.mma_async.sync.aligned.m64n96k16.f16.f16.f16 {%0,%1,%2,%3,%4,%5,%6,%7,%8,%9,%10,%11,%12,%13,%14,%15,%16,%17,%18,%19,%20,%21,%22,%23}, "
                     "{%24,%25,%26,%27}, %28, 0, 1, 1, 1;"
                     : "=r"(d[0]), "=r"(d[1]), "=r"(d[2]), "=r"(d[3]), "=r"(d[4]), "=r"(d[5]), "=r"(d[6]), "=r"(d[7]), "=r"(d[8]), "=r"(d[9]), "=r"(d[10]), "=r"(d[11]), "=r"(d[12]), "=r"(d[13]), "=r"(d[14]), "=r"(d[15]), "=r"(d[16]), "=r"(d[17]), "=r"(d[18]), "=r"(d[19]), "=r"(d[20]), "=r"(d[21]), "=r"(d[22]), "=r"(d[23])
                     : "r"(a0), "r"(a1), "r"(a2), "r"(a3), "l"(desc) : "memory");
    }
};

__device__ __forceinline__ void wgmma_stat(float (&d)[4], const uint32_t (&a)[4], uint64_t desc) {
    asm volatile("wgmma.mma_async.sync.aligned.m64n8k16.f32.bf16.bf16 {%0,%1,%2,%3}, {%4,%5,%6,%7}, %8, 0, 1, 1, 1;"
                 : "=f"(d[0]), "=f"(d[1]), "=f"(d[2]), "=f"(d[3]) : "r"(a[0]), "r"(a[1]), "r"(a[2]), "r"(a[3]), "l"(desc) : "memory");
}

__device__ __forceinline__ uint64_t make_desc(uint32_t addr, uint32_t lbo, uint32_t sbo) {
    return (uint64_t)((addr & 0x3FFFF) >> 4) | ((uint64_t)(lbo >> 4) << 16) | ((uint64_t)(sbo >> 4) << 32);
}

#define SCHED_FENCE() asm volatile("{\n\t.reg .pred p;\n\tsetp.ne.u32 p, %0, 0;\n\t@p exit;\n\t}" ::"r"(zero) : "memory")

__global__ void __launch_bounds__(NUM_THREADS, 1)
convnext_fused_kernel(const __grid_constant__ CUtensorMap xmap, const __grid_constant__ CUtensorMap w1map,
                      const __nv_bfloat16* __restrict__ dw, const __nv_bfloat16* __restrict__ w1,
                      const __nv_bfloat16* __restrict__ b1, const __nv_bfloat16* __restrict__ w2,
                      const __nv_bfloat16* __restrict__ b2, const __nv_bfloat16* __restrict__ gamma,
                      __nv_bfloat16* __restrict__ out, uint32_t zero) {
    extern __shared__ __align__(1024) uint8_t smem[];
    const uint32_t sbase = smem_u32(smem);
    const int tid = threadIdx.x;
    const int warp = __shfl_sync(0xffffffffu, tid >> 5, 0);
    const int lane = tid & 31;
    const int wg = warp >> 2, wr = warp & 3;
    const uint32_t bars = sbase + OFF_BAR;
    const int strip = blockIdx.x % NUM_STRIPS;
    const int band = blockIdx.x / NUM_STRIPS;
    const int dir = (band & 1) ? 1 : -1;
    const int ys = (band & 1) ? band * ROWS_PER_CTA - 1 : (band + 1) * ROWS_PER_CTA;

    auto load_row = [&](int j) {
        const uint32_t bar = bars + 8 * (BAR_ROW_FULL + (j & 3));
        const uint32_t dst = sbase + OFF_ROW + (j & 3) * ROW_BYTES;
        mbar_expect_tx(bar, 2 * HALF_BYTES);
        tma_load_3d(dst, &xmap, bar, 0, strip * STRIP_W - 1, ys + dir * j);
        tma_load_3d(dst + HALF_BOX, &xmap, bar, 0, strip * STRIP_W + 30, ys + dir * j);
    };
    auto load_w2 = [&](int s) {
        mbar_expect_tx(bars + 8 * (BAR_W2 + s), CH * HID / 2);
        bulk_load(sbase + OFF_W2 + s * (CH * HID / 2), w2 + s * (CH * HID / 4), CH * HID / 2, bars + 8 * (BAR_W2 + s));
    };
    if (warp == 11) {
        if (elect_one()) {
            asm volatile("prefetch.tensormap [%0];" ::"l"(reinterpret_cast<uint64_t>(&w1map)) : "memory");
#pragma unroll
            for (int s = 0; s < NUM_BARS; ++s)
                if (s < BAR_DONE || (s >= BAR_W1 && s <= BAR_DW)) mbar_init(bars + 8 * s, 1);
            asm volatile("fence.mbarrier_init.release.cluster;" ::: "memory");
        }
        __syncwarp();
        asm volatile("bar.arrive 2, %0;" ::"n"(NUM_THREADS) : "memory");
        if (elect_one()) {
#pragma unroll 1
            for (int s = 0; s < NCHUNK; ++s) {
                mbar_expect_tx(bars + 8 * (BAR_W1 + s), CH * NCH * 2);
                tma_load_2d(sbase + OFF_W1 + s * (CH * NCH * 2), &w1map, bars + 8 * (BAR_W1 + s), s * NCH, 0);
            }
            mbar_expect_tx(bars + 8 * BAR_DW, 9 * CH * 2);
            bulk_load(sbase + OFF_DW, dw, 9 * CH * 2, bars + 8 * BAR_DW);
            load_row(0);
            load_row(1);
            load_row(2);
#pragma unroll 1
            for (int s = 0; s < 4; ++s) load_w2(s);
            load_row(3);
        }
        __syncwarp();
        asm volatile("bar.sync 3, 64;" ::: "memory");
    } else if (warp == 9) {
        if (elect_one()) {
#pragma unroll
            for (int s = BAR_DONE; s < BAR_W1; ++s) mbar_init(bars + 8 * s, s < BAR_PRIME ? 8 : 4);
            mbar_init(bars + 8 * BAR_W1RDY, 4 * NMLP);
            mbar_init(bars + 8 * BAR_W2RDY, 8);
            asm volatile("mbarrier.arrive.shared::cta.b64 _, [%0], 4;" ::"r"(bars + 8 * BAR_DONE) : "memory");
        }
        __syncwarp();
        asm volatile("bar.arrive 3, 64;" ::: "memory");
    } else if (warp == 10) {
        if (elect_one()) asm volatile("prefetch.tensormap [%0];" ::"l"(reinterpret_cast<uint64_t>(&xmap)) : "memory");
    }

    if (wg == NMLP) {
        asm volatile("setmaxnreg.dec.sync.aligned.u32 128;");
        asm volatile("bar.sync 2, %0;" ::"n"(NUM_THREADS) : "memory");
        uint32_t w[3][3][3];
        {
            mbar_wait(bars + 8 * BAR_DW, 0);
            const uint32_t wp = sbase + OFF_DW + 48 * ((wr + (lane >> 2)) & 3) + 4 * (lane & 3) + 3 * (CH * 2);
#pragma unroll
            for (int s = 0; s < 3; ++s)
#pragma unroll
                for (int t = 0; t < 9; ++t) w[t / 3][t % 3][s] = lds32(wp + (t / 3 - 1) * dir * 3 * (CH * 2) + (t % 3) * (CH * 2) + s * 16);
        }
        const int ga = lane & 7, ja = lane >> 3;
        const uint32_t ip = sbase + OFF_ROW + (uint32_t)((ga >> 2) * HALF_OFF + (8 * (ga & 3) + ja) * (CH * 2) + 48 * ((wr + ga) & 3));
        const uint32_t op = sbase + OFF_A + (uint32_t)((ga >> 2) * A_HALF + (8 * (ga & 3) + ja) * A_PITCH + 48 * ((wr + ga) & 3));
        static_assert(NROW == 4 && NA == 2, "ring arithmetic");
        uint32_t P[2][3][8], f[10], c[8];
        auto load_window = [&](uint32_t a) {
            ldsm_x4(a, f[0], f[1], f[2], f[3]);
            ldsm_x4(a + 4 * (CH * 2), f[4], f[5], f[6], f[7]);
            ldsm_x2(a + 8 * (CH * 2), f[8], f[9]);
        };
        auto feed = [&](int e, int s, int i) {
#pragma unroll
            for (int o = i - 2; o <= i; ++o) {
                if (o < 0 || o > 7) continue;
                const int jx = i - o;
                if (jx == 0) {
                    asm volatile("fma.rn.bf16x2 %0, %3, %4, %1;\n\tfma.rn.bf16x2 %2, %3, %5, %2;\n\tmul.rn.bf16x2 %1, %3, %6;"
                                 : "=&r"(c[o]), "+r"(P[e][s][o]), "+r"(P[e ^ 1][s][o])
                                 : "r"(f[i]), "r"(w[2][0][s]), "r"(w[1][0][s]), "r"(w[0][0][s]));
                } else {
                    asm volatile("fma.rn.bf16x2 %0, %3, %4, %0;\n\tfma.rn.bf16x2 %2, %3, %5, %2;\n\tfma.rn.bf16x2 %1, %3, %6, %1;"
                                 : "+r"(c[o]), "+r"(P[e][s][o]), "+r"(P[e ^ 1][s][o])
                                 : "r"(f[i]), "r"(w[2][jx][s]), "r"(w[1][jx][s]), "r"(w[0][jx][s]));
                }
            }
        };
        __nv_bfloat16* xo = out + ((ys + dir) * IMG_W + strip * STRIP_W + wr * 16) * CH;
        const uint32_t xs = sbase + OFF_ROW + (wr >> 1) * HALF_OFF + ((wr & 1) * 16 + 1) * (CH * 2);
        mbar_wait(bars + 8 * BAR_ROW_FULL, 0);
#pragma unroll
        for (int r = 0; r < 2; ++r) {
            if (r == 1) {
                mbar_wait(bars + 8 * (BAR_ROW_FULL + 1), 0);
                if (elect_one()) bulk_store(xo, xs + ROW_BYTES, 16 * CH * 2);
                bulk_commit();
            }
#pragma unroll
            for (int s = 0; s < 3; ++s) {
                load_window(ip + r * ROW_BYTES + s * 16);
#pragma unroll
                for (int o = 0; o < 8; ++o) {
                    if (r == 1) P[0][s][o] = hfma2_bf16(f[o + 2], w[1][2][s], hfma2_bf16(f[o + 1], w[1][1][s], hfma2_bf16(f[o], w[1][0][s], P[0][s][o])));
                    P[r][s][o] = hfma2_bf16(f[o + 2], w[0][2][s], hfma2_bf16(f[o + 1], w[0][1][s], hmul2_bf16(f[o], w[0][0][s])));
                }
            }
        }
        __syncwarp();
        if (elect_one()) mbar_arrive(bars + 8 * BAR_PRIME);
        mbar_wait(bars + 8 * (BAR_ROW_FULL + 2), 0);
        load_window(ip + 2 * ROW_BYTES);
        uint32_t dbar = bars + 8 * BAR_DONE;
#pragma unroll 1
        for (int m = 0; m < ROWS_PER_CTA / 4; ++m) {
            const bool last = m + 1 == ROWS_PER_CTA / 4;
#pragma unroll
            for (int u = 0; u < 4; ++u) {
                const int j = 4 * m + u + 2;
                const int rs = (u + 2) & 3, ns = (u + 3) & 3;
                const uint32_t ebar = bars + 8 * (BAR_A_EMPTY + (u & 1)), rbar = bars + 8 * (BAR_ROW_FULL + ns);
                const uint32_t eph = ((u >> 1) & 1) ^ 1, rph = (m + (u >= 1)) & 1;
                xo += dir * IMG_W * CH;
                if (!(u == 3 && last)) {
                    if (elect_one()) bulk_store(xo, xs + rs * ROW_BYTES, 16 * CH * 2);
                }
                bulk_commit();
                bool ok = mbar_test(ebar, eph);
#pragma unroll
                for (int s = 0; s < 3; ++s) {
                    if (s == 2) ok = mbar_test(rbar, rph) || (u == 3 && last);
                    feed(u & 1, s, 0); feed(u & 1, s, 1); feed(u & 1, s, 2); feed(u & 1, s, 3);
                    if (s == 0) {
                        if (!ok) mbar_wait(ebar, eph);
                    }
                    const uint32_t nx = ip + (s == 2 ? ns : rs) * ROW_BYTES + ((s + 1) % 3) * 16;
                    const uint32_t ox = op + (u & 1) * A_BYTES + s * 16;
                    if (s < 2 || ok) ldsm_x4(nx, f[0], f[1], f[2], f[3]);
                    SCHED_FENCE();
                    feed(u & 1, s, 4); feed(u & 1, s, 5);
                    stsm_x4(ox, c[0], c[1], c[2], c[3]);
                    feed(u & 1, s, 6); feed(u & 1, s, 7);
                    ldsm_x4(nx + 4 * (CH * 2), f[4], f[5], f[6], f[7]);
                    SCHED_FENCE();
                    feed(u & 1, s, 8); feed(u & 1, s, 9);
                    stsm_x4(ox + 4 * A_PITCH, c[4], c[5], c[6], c[7]);
                    ldsm_x2(nx + 8 * (CH * 2), f[8], f[9]);
                    SCHED_FENCE();
                }
                bulk_wait<1>();
                __syncwarp();
                const bool el = elect_one();
                if (el) mbar_arrive(dbar);
                bulk_wait_read<0>();
                if (el) mbar_arrive(bars + 8 * (BAR_FREE + (u & 1)));
                dbar = dbar == bars + 8 * (BAR_DONE + NMLP - 1) ? bars + 8 * BAR_DONE : dbar + 8;
                if ((wr == u && !last) || (u == 0 && m == 0 && wr == 1)) {
                    mbar_wait(bars + 8 * (BAR_FREE + (u & 1)), (u >> 1) & 1);
                    if (elect_one()) load_row(u == 0 ? j + 4 - wr : j + 4);
                }
                if (!ok) {
                    mbar_wait(rbar, rph);
                    load_window(ip + ns * ROW_BYTES);
                }
            }
        }
    } else {
        const int g = lane >> 2, q = lane & 3;
        const uint4 r95 = __ldg(reinterpret_cast<const uint4*>(w1 + 95 * HID + (warp >> 1) * NCH + (lane & 7) * 8));
        const uint4 bb = __ldg(reinterpret_cast<const uint4*>(b1 + (warp >> 1) * NCH + (lane & 7) * 8));
        uint4 gm[3];
#pragma unroll
        for (int jj = 0; jj < 3; ++jj) gm[jj] = __ldg(reinterpret_cast<const uint4*>(gamma + jj * 32 + q * 8));
        uint32_t b2v = 0, g2v = 0;
        if (tid >= 128 && tid < 128 + CH / 2) {
            b2v = __ldg(reinterpret_cast<const uint32_t*>(b2) + tid - 128);
            g2v = __ldg(reinterpret_cast<const uint32_t*>(gamma) + tid - 128);
        }
        auto transform_w2 = [&](int s, int pass) {
            const uint32_t w2b = sbase + OFF_W2 + (warp - 4) * 6 * (8 * CH * 2);
            const float up = __uint_as_float((uint32_t)(127 + s) << 23), sc = up * GELU_INV2A;
            uint32_t gh[12];
#pragma unroll
            for (int e = 0; e < 12; ++e) {
                const uint32_t gv = (e & 3) == 0 ? gm[e / 4].x : (e & 3) == 1 ? gm[e / 4].y : (e & 3) == 2 ? gm[e / 4].z : gm[e / 4].w;
                gh[e] = pack_bf16(bf_lo(gv) * sc * 0x1p-112f, bf_hi(gv) * sc * 0x1p-112f);
            }
            if (tid < 128 + CH / 2) {
                const uint32_t v2 = pack_f16(bf_lo(b2v) * bf_lo(g2v) * up, bf_hi(b2v) * bf_hi(g2v) * up);
                const uint32_t a = sbase + OFF_B2I + (((tid >> 4) & 3) * 2 + ((tid >> 1) & 1)) * 64 + ((tid >> 2) & 3) * 16 + (tid & 1) * 8;
                sts32(a, v2); sts32(a + 4, v2);
            }
            mbar_wait(bars + 8 * (BAR_W2 + (warp >> 1) - 2), pass);
            uint4 v[3];
#pragma unroll
            for (int jj = 0; jj < 3; ++jj) v[jj] = lds128(w2b + g * (CH * 2) + jj * 64 + q * 16);
            uint32_t mu = 0, ms = 0;
#pragma unroll 1
            for (int i = 0; i < 6; ++i) {
                uint32_t o[12];
#pragma unroll
                for (int jj = 0; jj < 3; ++jj) {
                    mu = __vmaxu2(__vmaxu2(mu, v[jj].x), v[jj].y); mu = __vmaxu2(__vmaxu2(mu, v[jj].z), v[jj].w);
                    ms = __vmaxs2(__vmaxs2(ms, v[jj].x), v[jj].y); ms = __vmaxs2(__vmaxs2(ms, v[jj].z), v[jj].w);
                    o[jj * 4 + 0] = hmul2_bf16(v[jj].x, gh[jj * 4 + 0]);
                    o[jj * 4 + 1] = hmul2_bf16(v[jj].y, gh[jj * 4 + 1]);
                    o[jj * 4 + 2] = hmul2_bf16(v[jj].z, gh[jj * 4 + 2]);
                    o[jj * 4 + 3] = hmul2_bf16(v[jj].w, gh[jj * 4 + 3]);
                    if (i < 5) v[jj] = lds128(w2b + (i + 1) * (8 * CH * 2) + g * (CH * 2) + jj * 64 + q * 16);
                }
                __syncwarp();
#pragma unroll
                for (int e = 0; e < 12; ++e) o[e] = bf2_to_h2(o[e]);
#pragma unroll
                for (int jj = 0; jj < 3; ++jj)
                    stsm_x4(w2b + i * (8 * CH * 2) + jj * 512 + lane * 16, o[jj * 4], o[jj * 4 + 1], o[jj * 4 + 2], o[jj * 4 + 3]);
            }
            mu = __vmaxu2(mu & 0x7fff7fffu, ms);
            return __reduce_max_sync(0xffffffffu, max(mu & 0xffffu, mu >> 16));
        };
        if (warp != 11) asm volatile("bar.sync 2, %0;" ::"n"(NUM_THREADS) : "memory");
        asm volatile("setmaxnreg.inc.sync.aligned.u32 128;");
        {
            const int box = warp >> 1, cc = lane & 7, k0 = (warp & 1) * 48 + (lane >> 3);
            constexpr uint32_t DN = 0x07800780u;
            if (tid < 16) {
                const uint32_t v = tid < 8 ? 0x3F80u : 0x3F800000u;
                sts128(sbase + OFF_SEL + tid * 16, v, v, v, v);
            }
            const uint32_t m[4] = {hmul2_bf16(r95.x, DN | 0x80008000u), hmul2_bf16(r95.y, DN | 0x80008000u),
                                   hmul2_bf16(r95.z, DN | 0x80008000u), hmul2_bf16(r95.w, DN | 0x80008000u)};
            const uint32_t tb[4] = {scale2h(bb.x, GELU_A), scale2h(bb.y, GELU_A), scale2h(bb.z, GELU_A), scale2h(bb.w, GELU_A)};
            uint32_t mx = absmax2(absmax2(absmax2(absmax2(0, hmul2_bf16(bb.x, DN)), hmul2_bf16(bb.y, DN)), hmul2_bf16(bb.z, DN)), hmul2_bf16(bb.w, DN));
            uint32_t mg = 0;
#pragma unroll
            for (int jj = 0; jj < 3; ++jj) mg = absmax2(absmax2(absmax2(absmax2(mg, gm[jj].x), gm[jj].y), gm[jj].z), gm[jj].w);
            mg = __reduce_max_sync(0xffffffffu, max(mg & 0xffffu, mg >> 16));
            if (warp == 4 || warp == 5) {
                const uint32_t mb = __reduce_max_sync(0xffffffffu, max(b2v & 0x7fffu, (b2v >> 16) & 0x7fffu));
                if (lane == 0) sts32(sbase + OFF_MAX + 32 + warp * 4, mb);
            }
            const uint32_t wb = sbase + OFF_W1 + box * (CH * NCH * 2);
            const uint32_t wa[2] = {wb + k0 * 128 + ((cc ^ (k0 & 7)) << 4), wb + (k0 + 4) * 128 + ((cc ^ ((k0 + 4) & 7)) << 4)};
            mbar_wait(bars + 8 * (BAR_W1 + box), 0);
            uint4 u[2] = {lds128(wa[0]), lds128(wa[1])};
#pragma unroll 1
            for (int i = 0; i < 6; ++i) {
                uint32_t t[2][4];
#pragma unroll
                for (int e = 0; e < 2; ++e) {
                    t[e][0] = hfma2_bf16(u[e].x, DN, m[0]); t[e][1] = hfma2_bf16(u[e].y, DN, m[1]);
                    t[e][2] = hfma2_bf16(u[e].z, DN, m[2]); t[e][3] = hfma2_bf16(u[e].w, DN, m[3]);
                    if (i < 5) u[e] = lds128(wa[e] + (i + 1) * 1024);
#pragma unroll
                    for (int x = 0; x < 4; ++x) {
                        mx = absmax2(mx, t[e][x]);
                        t[e][x] = bf2_to_h2(t[e][x]);
                    }
                }
                sts128(wa[0] + i * 1024, t[0][0], t[0][1], t[0][2], t[0][3]);
                sts128(wa[1] + i * 1024, t[1][0], t[1][1], t[1][2], t[1][3]);
            }
            if (k0 + 44 == 95) sts128(wa[1] + 5 * 1024, tb[0], tb[1], tb[2], tb[3]);
            const uint32_t m1w = __reduce_max_sync(0xffffffffu, max(mx & 0xffffu, mx >> 16));
            if (lane == 0) sts32(sbase + OFF_MAX + warp * 4, m1w << 16);
            asm volatile("fence.proxy.async.shared::cta;" ::: "memory");
            __syncwarp();
            if (elect_one()) mbar_arrive(bars + 8 * BAR_W1RDY);
            if (wg > 0) {
                const uint32_t m2w = transform_w2(0, 0);
                if (lane == 0) sts32(sbase + OFF_MAX + warp * 4, m2w | (m1w << 16));
                asm volatile("fence.proxy.async.shared::cta;" ::: "memory");
                mbar_wait(bars + 8 * BAR_W1RDY, 0);
                asm volatile("bar.sync 1, 256;" ::: "memory");
                const uint32_t mm = lane < 14 ? lds32(sbase + OFF_MAX + lane * 4) : 0;
                const uint32_t m1 = __reduce_max_sync(0xffffffffu, lane < 12 ? mm >> 16 : 0);
                const uint32_t m2 = __reduce_max_sync(0xffffffffu, lane < 12 ? mm & 0xffffu : 0), mb = __reduce_max_sync(0xffffffffu, lane < 12 ? 0 : mm);
                const int e1 = max((int)(m1 >> 7), 1) - 14, eg = (int)(mg >> 7) - 126, ew = (int)(m2 >> 7) - 126;
                const int e2 = ew + eg + 1, eb = (int)(mb >> 7) - 126 + eg;
                int s = min(min(-1 - e1 - e2, 14 - eb), 14 - e2);
                if (s >= 0 && s <= 12 && e2 >= -9 && eg >= -9) s = 0;
                s = min(max(s, -120), min(120, 120 - eg));
                if (s != 0) {
                    if ((warp & 1) == 0 && elect_one()) load_w2((warp >> 1) - 2);
                    transform_w2(s, 1);
                    asm volatile("fence.proxy.async.shared::cta;" ::: "memory");
                }
                if (tid == 128) sts32(sbase + OFF_MAX + 64, (uint32_t)(127 - s) * 0x00800080u);
                __syncwarp();
                if (elect_one()) mbar_arrive(bars + 8 * BAR_W2RDY);
            } else if (wr == 0) {
                mbar_wait(bars + 8 * BAR_PRIME, 0);
                if (elect_one()) load_row(4);
            }
        }
        const uint64_t descW1 = make_desc(sbase + OFF_W1, CH * NCH * 2, 1024) | (1ull << 62);
        const uint64_t descW2 = make_desc(sbase + OFF_W2, (CH / 8) * 128, 128);
        const uint64_t descS = make_desc(sbase + OFF_SEL, 128, 128);
        uint32_t la = sbase + OFF_A + (wg & 1) * A_BYTES + wr * 16 * A_PITCH + (wr >> 1) * 64 +
                      (uint32_t)(((lane & 7) + ((lane >> 3) & 1) * 8) * A_PITCH + (lane >> 4) * 16);

        uint32_t acc2[24];
        uint32_t h[2][NCH / 4];
        uint32_t a1[6][4];
        uint32_t pp[4];
        float st[4];

        auto load_a = [&]() {
#pragma unroll
            for (int kb = 0; kb < 6; ++kb) ldsm_x4(la + kb * 32, a1[kb][0], a1[kb][1], a1[kb][2], a1[kb][3]);
        };
        auto partial_a = [&](int i) {
            uint32_t s = hadd2_bf16(hadd2_bf16(hadd2_bf16(a1[0][i], a1[1][i]), hadd2_bf16(a1[2][i], a1[3][i])), hadd2_bf16(a1[4][i], a1[5][i]));
            uint32_t v = hmul2_bf16(a1[0][i], a1[0][i]);
#pragma unroll
            for (int kb = 1; kb < 6; ++kb) v = hfma2_bf16(a1[kb][i], a1[kb][i], v);
            if (i >= 2) { s = hadd2_bf16(s, pp[i & 1]); v = hadd2_bf16(v, pp[2 + (i & 1)]); }
            asm volatile("" : "+r"(s), "+r"(v));
            pp[i & 1] = s; pp[2 + (i & 1)] = v;
        };
        uint32_t sel95 = q == 3 ? 0x7610 : 0x3210;
        asm volatile("" : "+r"(sel95));
        auto norm_a = [&]() {
            constexpr float K = GELU_A * 0x1p-112f, SQ = 9.797958971132712f;
            float m0 = st[0] * (-1.f / CH), m1 = st[2] * (-1.f / CH);
            float r0, r1;
            asm("rsqrt.approx.ftz.f32 %0, %1;" : "=f"(r0) : "f"(fmaxf(fmaf(m0, st[0], st[1]), 0.f) + CH * 1e-5f));
            asm("rsqrt.approx.ftz.f32 %0, %1;" : "=f"(r1) : "f"(fmaxf(fmaf(m1, st[2], st[3]), 0.f) + CH * 1e-5f));
            const uint32_t rp = pack_bf16(r0 * (K * SQ), r1 * (K * SQ));
            const float o0 = m0 * bf_lo(rp), o1 = m1 * bf_hi(rp);
            const uint32_t op = pack_bf16(o0, o1);
            const bool easy = (fmaxf(fabsf(o0), fabsf(o1)) < 0.5f * K) & (fminf(r0, r1) > 0x1p-12f);
            if (__all_sync(0xffffffffu, easy)) {
#pragma unroll
                for (int kb = 0; kb < 6; ++kb)
#pragma unroll
                    for (int i = 0; i < 4; ++i)
                        a1[kb][i] = bf2_to_h2((i & 1) ? hfma2_bf16_bcast<true>(a1[kb][i], rp, op) : hfma2_bf16_bcast<false>(a1[kb][i], rp, op));
            } else {
                float s0[2] = {0.f, 0.f}, s1[2] = {0.f, 0.f}, v0[2] = {0.f, 0.f}, v1[2] = {0.f, 0.f};
#pragma unroll
                for (int kb = 0; kb < 6; ++kb)
#pragma unroll
                    for (int i = 0; i < 2; ++i) {
                        float a = bf_lo(a1[kb][2 * i]), b = bf_hi(a1[kb][2 * i]);
                        s0[0] += a; v0[0] = fmaf(a, a, v0[0]); s0[1] += b; v0[1] = fmaf(b, b, v0[1]);
                        a = bf_lo(a1[kb][2 * i + 1]); b = bf_hi(a1[kb][2 * i + 1]);
                        s1[0] += a; v1[0] = fmaf(a, a, v1[0]); s1[1] += b; v1[1] = fmaf(b, b, v1[1]);
                    }
                float sa = s0[0] + s0[1], sb = s1[0] + s1[1], va = v0[0] + v0[1], vb = v1[0] + v1[1];
                sa += __shfl_xor_sync(0xffffffffu, sa, 1); sb += __shfl_xor_sync(0xffffffffu, sb, 1);
                va += __shfl_xor_sync(0xffffffffu, va, 1); vb += __shfl_xor_sync(0xffffffffu, vb, 1);
                sa += __shfl_xor_sync(0xffffffffu, sa, 2); sb += __shfl_xor_sync(0xffffffffu, sb, 2);
                va += __shfl_xor_sync(0xffffffffu, va, 2); vb += __shfl_xor_sync(0xffffffffu, vb, 2);
                m0 = sa * (1.f / CH); m1 = sb * (1.f / CH);
                asm("rsqrt.approx.ftz.f32 %0, %1;" : "=f"(r0) : "f"(fmaxf(fmaf(-m0, m0, va * (1.f / CH)), 0.f) + 1e-5f));
                asm("rsqrt.approx.ftz.f32 %0, %1;" : "=f"(r1) : "f"(fmaxf(fmaf(-m1, m1, vb * (1.f / CH)), 0.f) + 1e-5f));
                r0 *= GELU_A; r1 *= GELU_A;
                const float p0 = -m0 * r0, p1 = -m1 * r1;
#pragma unroll
                for (int kb = 0; kb < 6; ++kb)
#pragma unroll
                    for (int i = 0; i < 4; ++i) {
                        const float r = (i & 1) ? r1 : r0, o = (i & 1) ? p1 : p0;
                        a1[kb][i] = pack_f16(fmaf(bf_lo(a1[kb][i]), r, o), fmaf(bf_hi(a1[kb][i]), r, o));
                    }
            }
            a1[5][2] = __byte_perm(a1[5][2], 0x3C000000u, sel95);
            a1[5][3] = __byte_perm(a1[5][3], 0x3C000000u, sel95);
        };
        auto gemm1 = [&](int c, int k0, int k1) {
#pragma unroll
            for (int kk = k0; kk < k1; ++kk) {
                if (kk == 0) WH<NCH>::first(h[c & 1], a1[0][0], a1[0][1], a1[0][2], a1[0][3], descW1 + (uint64_t)(c * 768));
                else WH<NCH>::acc(h[c & 1], a1[kk][0], a1[kk][1], a1[kk][2], a1[kk][3], descW1 + (uint64_t)(c * 768 + kk * 128));
            }
        };
        auto gemm2 = [&](int c, int k0, int k1) {
#pragma unroll
            for (int kk = k0; kk < k1; ++kk)
                WH<96>::acc(acc2, h[c & 1][kk * 4], h[c & 1][kk * 4 + 1], h[c & 1][kk * 4 + 2], h[c & 1][kk * 4 + 3],
                            descW2 + (uint64_t)(((c * (NCH / 8) + 2 * kk) * (CH / 8)) * 8));
        };
        uint32_t b2a = sbase + OFF_B2I + q * 16;
        asm volatile("" : "+r"(b2a));

        mbar_wait(bars + 8 * BAR_W1RDY, 0);
        static_assert((OFF_BAR + 8 * BAR_A_EMPTY) % 16 == 0 && (NMLP & 1), "the conv-tile slot alternates");
        const uint32_t nbar = bars + 8 * (BAR_DONE + wg), tbar = bars + 8 * (BAR_DONE + (wg + 1) % NMLP);
        uint32_t ebar = bars + 8 * (BAR_A_EMPTY + (wg & 1)), nph = 0;
        const uint32_t lsum = 2 * la + ((wg & 1) ? -A_BYTES : A_BYTES);
        mbar_wait(nbar, 0);
        load_a();
#pragma unroll
        for (int i = 0; i < 4; ++i) partial_a(i);
        wg_fence();
        wgmma_stat(st, pp, descS);
        wg_commit();
        __syncwarp();
        if (elect_one()) {
            mbar_arrive(ebar);
            mbar_arrive(tbar);
        }
        wg_wait<0>();
        fence_regs(st);
        norm_a();
        wg_fence();
        gemm1(0, 0, 6);
        wg_commit();
        mbar_wait(bars + 8 * BAR_W2RDY, 0);
        const uint32_t oscale = lds32(sbase + OFF_MAX + 64);
        wg_wait<0>();
        uint32_t y[24];
#pragma unroll
        for (int i = 0; i < 24; ++i) y[i] = 0;
        __nv_bfloat16* optr = out + ((ys + dir * (wg + 1)) * IMG_W + strip * STRIP_W + wr * 16 + g) * CH + q * 8;
        auto red_y = [&](int i, uint64_t pol) {
            const int jj = i / 2, hrow = i % 2;
            red_add_bf16x8(optr + hrow * 8 * CH + jj * 32, y[jj * 8 + hrow], y[jj * 8 + hrow + 2], y[jj * 8 + hrow + 4], y[jj * 8 + hrow + 6], pol);
        };
#pragma unroll 1
        for (int t = wg;; t += NMLP) {
            const bool more = t + NMLP < ROWS_PER_CTA;
            bool ready = true;
            const uint64_t rpol = t != wg ? policy_evict_first() : policy_evict_normal();
            SCHED_FENCE();
            constexpr int P = NCH / 4, NP = HID / 4;
            uint32_t zz[2];
            uint16_t t0[LAG], t1[LAG];
#pragma unroll
            for (int G = 0; G <= NP + LAG; ++G) {
                const int ca = G / P, gp = G % P;
                if (G == TESTPOS) ready = mbar_test(nbar, nph) || !more;
                if (G == NP - P && !ready) mbar_wait(nbar, nph);
                if (gp == 0 && ca >= 1 && G < NP) { wg_wait<1>(); fence_regs(h[ca & 1]); }
                if (G == NP - P) load_a();
                if (ca + 1 < NCHUNK && gp == (ca == 0 ? 1 : G1PA)) {
                    if (ca > 0) wg_wait<0>();
                    wg_fence();
                    gemm1(ca + 1, 0, 3);
                }
                if (ca + 1 < NCHUNK && gp == (ca == 0 ? 3 : G1PB)) {
                    wg_fence();
                    gemm1(ca + 1, 3, 6);
                    wg_commit();
                }
                if (ca < NCHUNK && gp == G2PA) {
                    fence_regs(h[ca & 1]);
                    wg_fence();
                    if (G == STATPOS) wgmma_stat(st, pp, descS);
                    gemm2(ca, 0, 2);
                    wg_commit();
                }
                if (ca >= 1 && gp == G2PB - P) {
                    fence_regs(h[(ca - 1) & 1]);
                    wg_fence();
                    gemm2(ca - 1, 2, 4);
                    wg_commit();
                }
                if (G == INITPOS) {
#pragma unroll
                    for (int m = 0; m < 6; ++m) {
                        const uint4 v = lds128(b2a + m * 64);
                        acc2[4 * m] = v.x; acc2[4 * m + 1] = v.y; acc2[4 * m + 2] = v.z; acc2[4 * m + 3] = v.w;
                    }
                }
                if (G == RELPOS) {
                    __syncwarp();
                    if (elect_one() & more) mbar_arrive(ebar);
                }
                if (G >= REDPOS && G < REDPOS + 6 * REDSTEP && (G - REDPOS) % REDSTEP == 0) red_y((G - REDPOS) / REDSTEP, rpol);
                if (G == 4 * P + 4) {
                    asm volatile("sub.u32 %0, %1, %0;" : "+r"(la) : "r"(lsum));
                    ebar ^= 8;
                    nph ^= 1;
                    asm volatile("add.u64 %0, %0, %1;" : "+l"(optr) : "l"(t == wg ? 0ll : (long long)dir * (NMLP * IMG_W * CH * 2)));
                }
                if (G >= STATPOS - 4 && G < STATPOS) partial_a(G - (STATPOS - 4));
                int e = G - LAG;
                if (e >= 0 && e < NP) {
                    uint32_t& v = h[(e / P) & 1][e % P];
                    uint32_t o;
                    asm volatile("{\n\t.reg .b32 t;\n\tmov.b32 t, {%2, %3};\n\tfma.rn.f16x2 %0, %1, t, %1;\n\t}"
                                 : "=r"(o) : "r"(v), "h"(t0[e % LAG]), "h"(t1[e % LAG]));
                    v = o;
                }
                e = G - 1;
                if (e >= 0 && e < NP)
                    asm volatile("{\n\t.reg .b16 l, h;\n\tmov.b32 {l, h}, %2;\n\ttanh.approx.f16 %0, l;\n\ttanh.approx.f16 %1, h;\n\t}"
                                 : "=h"(t0[e % LAG]), "=h"(t1[e % LAG]) : "r"(zz[e & 1]));
                if (G < NP)
                    asm volatile("{\n\t.reg .b32 p;\n\tfma.rn.f16x2 p, %1, %1, %2;\n\tmul.rn.f16x2 %0, %1, p;\n\t}"
                                 : "=r"(zz[G & 1]) : "r"(h[ca & 1][gp]), "r"(0x40D940D9u));
                SCHED_FENCE();
            }
            if (!more) break;
            wg_wait<1>();
            fence_regs(st);
            norm_a();
            if (elect_one()) mbar_arrive(tbar);
            wg_fence();
            gemm1(0, 0, 6);
            wg_commit();
            SCHED_FENCE();
            wg_wait<1>();
            fence_regs(acc2);
#pragma unroll
            for (int i = 0; i < 24; ++i) y[i] = h2_to_bf2(acc2[i]);
            if (oscale != 0x3F803F80u) {
#pragma unroll
                for (int i = 0; i < 24; ++i) y[i] = hmul2_bf16(y[i], oscale);
            }
            wg_wait<0>();
        }
        wg_wait<0>();
        fence_regs(acc2);
#pragma unroll
        for (int i = 0; i < 24; ++i) y[i] = hmul2_bf16(h2_to_bf2(acc2[i]), oscale);
#pragma unroll
        for (int i = 0; i < 6; ++i) red_y(i, policy_evict_normal());
    }
}

typedef CUresult (*PFN_encodeTiled)(CUtensorMap*, CUtensorMapDataType, cuuint32_t, void*, const cuuint64_t*,
                                    const cuuint64_t*, const cuuint32_t*, const cuuint32_t*, CUtensorMapInterleave,
                                    CUtensorMapSwizzle, CUtensorMapL2promotion, CUtensorMapFloatOOBfill);

}

extern "C" void kernel_launch(void* const* d_in, const int* in_sizes, int n_in, void* d_out, int out_size) {
    const __nv_bfloat16* x = (const __nv_bfloat16*)d_in[0];
    const __nv_bfloat16* dw = (const __nv_bfloat16*)d_in[1];
    const __nv_bfloat16* w1 = (const __nv_bfloat16*)d_in[2];
    const __nv_bfloat16* b1 = (const __nv_bfloat16*)d_in[3];
    const __nv_bfloat16* w2 = (const __nv_bfloat16*)d_in[4];
    const __nv_bfloat16* b2 = (const __nv_bfloat16*)d_in[5];
    const __nv_bfloat16* gamma = (const __nv_bfloat16*)d_in[6];
    __nv_bfloat16* out = (__nv_bfloat16*)d_out;

    static PFN_encodeTiled encode = nullptr;
    if (!encode) {
        void* fn = nullptr;
        cudaDriverEntryPointQueryResult qres;
        cudaGetDriverEntryPoint("cuTensorMapEncodeTiled", &fn, cudaEnableDefault, &qres);
        encode = (PFN_encodeTiled)fn;
        cudaFuncSetAttribute(convnext_fused_kernel, cudaFuncAttributeMaxDynamicSharedMemorySize, SMEM_BYTES);
    }
    CUtensorMap xmap, w1map;
    cuuint64_t gdim[3] = {CH, IMG_W, IMG_H};
    cuuint64_t gstr[2] = {CH * 2, (cuuint64_t)IMG_W * CH * 2};
    cuuint32_t box[3] = {CH, HALF_W, 1};
    cuuint32_t estr[3] = {1, 1, 1};
    encode(&xmap, CU_TENSOR_MAP_DATA_TYPE_BFLOAT16, 3, (void*)x, gdim, gstr, box, estr, CU_TENSOR_MAP_INTERLEAVE_NONE,
           CU_TENSOR_MAP_SWIZZLE_NONE, CU_TENSOR_MAP_L2_PROMOTION_L2_128B, CU_TENSOR_MAP_FLOAT_OOB_FILL_NONE);
    cuuint64_t wdim[2] = {HID, CH};
    cuuint64_t wstr[1] = {HID * 2};
    cuuint32_t wbox[2] = {NCH, CH};
    encode(&w1map, CU_TENSOR_MAP_DATA_TYPE_BFLOAT16, 2, (void*)w1, wdim, wstr, wbox, estr, CU_TENSOR_MAP_INTERLEAVE_NONE,
           CU_TENSOR_MAP_SWIZZLE_128B, CU_TENSOR_MAP_L2_PROMOTION_L2_256B, CU_TENSOR_MAP_FLOAT_OOB_FILL_NONE);

    convnext_fused_kernel<<<NUM_CTAS, NUM_THREADS, SMEM_BYTES>>>(xmap, w1map, dw, w1, b1, w2, b2, gamma, out, 0u);
}
```

```cpp
#include <cuda_runtime.h>
#include <cuda_bf16.h>
#include <cuda.h>
#include <stdint.h>

namespace {

constexpr int IMG_H = 512, IMG_W = 512, CH = 96, HID = 384;
constexpr int STRIP_W = 64;
constexpr int NUM_STRIPS = IMG_W / STRIP_W;
constexpr int ROWS_PER_CTA = 32;
constexpr int NUM_CTAS = NUM_STRIPS * (IMG_H / ROWS_PER_CTA);
constexpr int HALF_W = STRIP_W / 2 + 3;
constexpr int HALF_BYTES = HALF_W * CH * 2;
constexpr int HALF_BOX = ((HALF_BYTES + 127) / 128) * 128;
constexpr int HALF_OFF = HALF_BOX + CH * 2;
constexpr int ROW_BYTES = 2 * HALF_BOX;
constexpr int NROW = 4;
constexpr int NA = 2;
constexpr int A_PITCH = CH * 2 + 16;
constexpr int A_HALF = 32 * A_PITCH + 64;
constexpr int A_BYTES = ((A_HALF + 32 * A_PITCH + 127) / 128) * 128;
constexpr int NCH = 64;
constexpr int NCHUNK = HID / NCH;
constexpr int NMLP = 3;

#define G1PA_ 7
#define G1PB_ 10
#define G2PA_ 13
#define RELPOS_ 94
#define REDPOS_ 8
#define REDSTEP_ 6
constexpr int LAG = 3;
constexpr int G1PA = G1PA_, G1PB = G1PB_;
constexpr int G2PA = G2PA_, G2PB = 16 + LAG;
constexpr int INITPOS = 2, REDPOS = REDPOS_, REDSTEP = REDSTEP_, TESTPOS = 76, RELPOS = RELPOS_;
constexpr int STATPOS = 80 + G2PA;
static_assert(G1PA < G1PB && G1PB < G2PA && G2PA >= 8 + LAG && G2PA < 16 && RELPOS >= STATPOS, "schedule");

constexpr int OFF_W1 = 0;
constexpr int OFF_W2 = OFF_W1 + CH * HID * 2;
constexpr int OFF_ROW = OFF_W2 + CH * HID * 2;
constexpr int OFF_A = OFF_ROW + NROW * ROW_BYTES;
constexpr int OFF_SEL = OFF_A + NA * A_BYTES;
constexpr int OFF_B2I = OFF_SEL + 256;
constexpr int OFF_MAX = OFF_B2I + 768;
constexpr int OFF_DW = OFF_MAX + 128;
constexpr int OFF_BAR = OFF_DW + 9 * CH * 2;
constexpr int BAR_ROW_FULL = 0, BAR_DONE = NROW, BAR_PRIME = BAR_DONE + NMLP, BAR_FREE = BAR_PRIME + 1, BAR_A_EMPTY = BAR_FREE + 2;
constexpr int BAR_W1 = BAR_A_EMPTY + NA, BAR_W2 = BAR_W1 + NCHUNK, BAR_DW = BAR_W2 + 4;
constexpr int BAR_W1RDY = BAR_DW + 1, BAR_W2RDY = BAR_W1RDY + 1;
constexpr int NUM_BARS = BAR_W2RDY + 1;
constexpr int SMEM_BYTES = OFF_BAR + NUM_BARS * 8;
static_assert(SMEM_BYTES <= 232448, "smem");
static_assert(HALF_OFF % 128 == 64 && OFF_ROW % 128 == 0 && OFF_SEL % 128 == 0 && OFF_B2I % 128 == 0, "bank layout");

constexpr int NUM_THREADS = 128 * (NMLP + 1);

constexpr float GELU_A = 0.7978845608028654f / 2.423828125f;
constexpr float GELU_INV2A = 0.5f / GELU_A;

__device__ __forceinline__ uint32_t smem_u32(const void* p) { return (uint32_t)__cvta_generic_to_shared(p); }

__device__ __forceinline__ void mbar_init(uint32_t bar, uint32_t count) {
    asm volatile("mbarrier.init.shared::cta.b64 [%0], %1;" ::"r"(bar), "r"(count) : "memory");
}
__device__ __forceinline__ void mbar_expect_tx(uint32_t bar, uint32_t bytes) {
    asm volatile("mbarrier.arrive.expect_tx.shared::cta.b64 _, [%0], %1;" ::"r"(bar), "r"(bytes) : "memory");
}
__device__ __forceinline__ void mbar_arrive(uint32_t bar) {
    asm volatile("mbarrier.arrive.shared::cta.b64 _, [%0];" ::"r"(bar) : "memory");
}
__device__ __forceinline__ bool mbar_test(uint32_t bar, uint32_t parity) {
    uint32_t done;
    asm volatile(
        "{\n\t.reg .pred p;\n\t"
        "mbarrier.test_wait.parity.shared::cta.b64 p, [%1], %2;\n\t"
        "selp.u32 %0, 1, 0, p;\n\t}"
        : "=r"(done) : "r"(bar), "r"(parity) : "memory");
    return done != 0;
}
__device__ __forceinline__ void mbar_wait(uint32_t bar, uint32_t parity) {
    for (int it = 0; it < (1 << 20); ++it) {
        uint32_t done;
        asm volatile(
            "{\n\t.reg .pred p;\n\t"
            "mbarrier.try_wait.parity.shared::cta.b64 p, [%1], %2;\n\t"
            "selp.u32 %0, 1, 0, p;\n\t}"
            : "=r"(done) : "r"(bar), "r"(parity) : "memory");
        if (done) break;
    }
}
__device__ __forceinline__ uint64_t policy_evict_first() {
    uint64_t p;
    asm("createpolicy.fractional.L2::evict_first.b64 %0, 1.0;" : "=l"(p));
    return p;
}
__device__ __forceinline__ uint64_t policy_evict_normal() {
    uint64_t p;
    asm("createpolicy.fractional.L2::evict_normal.b64 %0, 1.0;" : "=l"(p));
    return p;
}
__device__ __forceinline__ void tma_load_3d(uint32_t dst, const CUtensorMap* map, uint32_t bar, int c0, int c1, int c2) {
    asm volatile(
        "cp.async.bulk.tensor.3d.shared::cluster.global.mbarrier::complete_tx::bytes.L2::cache_hint [%0], [%1, {%3, %4, %5}], [%2], %6;"
        ::"r"(dst), "l"(reinterpret_cast<uint64_t>(map)), "r"(bar), "r"(c0), "r"(c1), "r"(c2), "l"(policy_evict_first()) : "memory");
}
__device__ __forceinline__ void tma_load_2d(uint32_t dst, const CUtensorMap* map, uint32_t bar, int c0, int c1) {
    asm volatile(
        "cp.async.bulk.tensor.2d.shared::cluster.global.mbarrier::complete_tx::bytes [%0], [%1, {%3, %4}], [%2];"
        ::"r"(dst), "l"(reinterpret_cast<uint64_t>(map)), "r"(bar), "r"(c0), "r"(c1) : "memory");
}
__device__ __forceinline__ bool elect_one() {
    uint32_t p;
    asm volatile("{\n\t.reg .pred p;\n\telect.sync _|p, 0xffffffff;\n\tselp.u32 %0, 1, 0, p;\n\t}" : "=r"(p));
    return p != 0;
}
__device__ __forceinline__ void bulk_load(uint32_t dst, const void* src, uint32_t bytes, uint32_t bar) {
    asm volatile("cp.async.bulk.shared::cluster.global.mbarrier::complete_tx::bytes [%0], [%1], %2, [%3];"
                 ::"r"(dst), "l"(src), "r"(bytes), "r"(bar) : "memory");
}
__device__ __forceinline__ void bulk_store(void* dst, uint32_t src, uint32_t bytes) {
    asm volatile("cp.async.bulk.global.shared::cta.bulk_group [%0], [%1], %2;" ::"l"(dst), "r"(src), "r"(bytes) : "memory");
}
__device__ __forceinline__ void bulk_commit() { asm volatile("cp.async.bulk.commit_group;" ::: "memory"); }
template <int N> __device__ __forceinline__ void bulk_wait_read() {
    asm volatile("cp.async.bulk.wait_group.read %0;" ::"n"(N) : "memory");
}
template <int N> __device__ __forceinline__ void bulk_wait() {
    asm volatile("cp.async.bulk.wait_group %0;" ::"n"(N) : "memory");
}
__device__ __forceinline__ void ldsm_x4(uint32_t addr, uint32_t& r0, uint32_t& r1, uint32_t& r2, uint32_t& r3) {
    asm volatile("ldmatrix.sync.aligned.m8n8.x4.shared.b16 {%0,%1,%2,%3}, [%4];"
                 : "=r"(r0), "=r"(r1), "=r"(r2), "=r"(r3) : "r"(addr) : "memory");
}
__device__ __forceinline__ void ldsm_x2(uint32_t addr, uint32_t& r0, uint32_t& r1) {
    asm volatile("ldmatrix.sync.aligned.m8n8.x2.shared.b16 {%0,%1}, [%2];" : "=r"(r0), "=r"(r1) : "r"(addr) : "memory");
}
__device__ __forceinline__ void stsm_x4(uint32_t addr, uint32_t r0, uint32_t r1, uint32_t r2, uint32_t r3) {
    asm volatile("stmatrix.sync.aligned.m8n8.x4.shared.b16 [%0], {%1,%2,%3,%4};"
                 ::"r"(addr), "r"(r0), "r"(r1), "r"(r2), "r"(r3) : "memory");
}
__device__ __forceinline__ uint4 lds128(uint32_t addr) {
    uint4 v;
    asm volatile("ld.shared.v4.u32 {%0,%1,%2,%3}, [%4];" : "=r"(v.x), "=r"(v.y), "=r"(v.z), "=r"(v.w) : "r"(addr) : "memory");
    return v;
}
__device__ __forceinline__ uint32_t lds32(uint32_t addr) {
    uint32_t a;
    asm volatile("ld.shared.u32 %0, [%1];" : "=r"(a) : "r"(addr) : "memory");
    return a;
}
__device__ __forceinline__ void sts32(uint32_t addr, uint32_t a) {
    asm volatile("st.shared.u32 [%0], %1;" ::"r"(addr), "r"(a) : "memory");
}
__device__ __forceinline__ void sts128(uint32_t addr, uint32_t a, uint32_t b, uint32_t c, uint32_t d) {
    asm volatile("st.shared.v4.u32 [%0], {%1,%2,%3,%4};" ::"r"(addr), "r"(a), "r"(b), "r"(c), "r"(d) : "memory");
}
__device__ __forceinline__ uint32_t hfma2_bf16(uint32_t a, uint32_t b, uint32_t c) {
    uint32_t d;
    asm("fma.rn.bf16x2 %0, %1, %2, %3;" : "=r"(d) : "r"(a), "r"(b), "r"(c));
    return d;
}
template <bool HI> __device__ __forceinline__ uint32_t hfma2_bf16_bcast(uint32_t a, uint32_t b, uint32_t c) {
    uint32_t d;
    if (HI)
        asm("{\n\t.reg .b16 a, b, c, d;\n\t.reg .b32 r, o;\n\tmov.b32 {a, b}, %2;\n\tmov.b32 {c, d}, %3;\n\t"
            "mov.b32 r, {b, b};\n\tmov.b32 o, {d, d};\n\tfma.rn.bf16x2 %0, %1, r, o;\n\t}" : "=r"(d) : "r"(a), "r"(b), "r"(c));
    else
        asm("{\n\t.reg .b16 a, b, c, d;\n\t.reg .b32 r, o;\n\tmov.b32 {a, b}, %2;\n\tmov.b32 {c, d}, %3;\n\t"
            "mov.b32 r, {a, a};\n\tmov.b32 o, {c, c};\n\tfma.rn.bf16x2 %0, %1, r, o;\n\t}" : "=r"(d) : "r"(a), "r"(b), "r"(c));
    return d;
}
__device__ __forceinline__ uint32_t hmul2_bf16(uint32_t a, uint32_t b) {
    uint32_t d;
    asm("mul.rn.bf16x2 %0, %1, %2;" : "=r"(d) : "r"(a), "r"(b));
    return d;
}
__device__ __forceinline__ uint32_t hadd2_bf16(uint32_t a, uint32_t b) {
    uint32_t d;
    asm("add.rn.bf16x2 %0, %1, %2;" : "=r"(d) : "r"(a), "r"(b));
    return d;
}
__device__ __forceinline__ float bf_lo(uint32_t v) { return __uint_as_float(v << 16); }
__device__ __forceinline__ float bf_hi(uint32_t v) { return __uint_as_float(v & 0xffff0000u); }
__device__ __forceinline__ uint32_t pack_bf16(float lo, float hi) {
    uint32_t d;
    asm("cvt.rn.bf16x2.f32 %0, %1, %2;" : "=r"(d) : "f"(hi), "f"(lo));
    return d;
}
__device__ __forceinline__ uint32_t pack_f16(float lo, float hi) {
    uint32_t d;
    asm("cvt.rn.f16x2.f32 %0, %1, %2;" : "=r"(d) : "f"(hi), "f"(lo));
    return d;
}
__device__ __forceinline__ uint32_t scale2h(uint32_t v, float s) {
    return pack_f16(bf_lo(v) * s, bf_hi(v) * s);
}
__device__ __forceinline__ uint32_t h2_to_bf2(uint32_t v) {
    uint32_t d;
    asm("{\n\t.reg .b16 l, h;\n\t.reg .f32 a, b;\n\tmov.b32 {l, h}, %1;\n\tcvt.f32.f16 a, l;\n\tcvt.f32.f16 b, h;\n\t"
        "cvt.rn.bf16x2.f32 %0, b, a;\n\t}" : "=r"(d) : "r"(v));
    return d;
}
__device__ __forceinline__ uint32_t bf2_to_h2(uint32_t y) { return (y & 0x7fff7fffu) * 7u + y; }
__device__ __forceinline__ uint32_t absmax2(uint32_t m, uint32_t v) { return __vmaxu2(m, v & 0x7fff7fffu); }
__device__ __forceinline__ void red_add_bf16x8(void* p, uint32_t a, uint32_t b, uint32_t c, uint32_t d, uint64_t pol) {
    asm volatile("red.global.add.noftz.L2::cache_hint.v4.bf16x2 [%0], {%1,%2,%3,%4}, %5;"
                 ::"l"(p), "r"(a), "r"(b), "r"(c), "r"(d), "l"(pol) : "memory");
}
__device__ __forceinline__ void wg_fence() { asm volatile("wgmma.fence.sync.aligned;" ::: "memory"); }
__device__ __forceinline__ void wg_commit() { asm volatile("wgmma.commit_group.sync.aligned;" ::: "memory"); }
template <int N> __device__ __forceinline__ void wg_wait() {
    asm volatile("wgmma.wait_group.sync.aligned %0;" ::"n"(N) : "memory");
}
template <int N> __device__ __forceinline__ void fence_regs(float (&d)[N]) {
#pragma unroll
    for (int i = 0; i < N; ++i) asm volatile("" : "+f"(d[i])::"memory");
}
template <int N> __device__ __forceinline__ void fence_regs(uint32_t (&d)[N]) {
#pragma unroll
    for (int i = 0; i < N; ++i) asm volatile("" : "+r"(d[i])::"memory");
}

template <int N> struct WH;
template <> struct WH<64> {
    static __device__ __forceinline__ void acc(uint32_t* d, uint32_t a0, uint32_t a1, uint32_t a2, uint32_t a3, uint64_t desc) {
        asm volatile("wgmma.mma_async.sync.aligned.m64n64k16.f16.f16.f16 {%0,%1,%2,%3,%4,%5,%6,%7,%8,%9,%10,%11,%12,%13,%14,%15}, "
                     "{%16,%17,%18,%19}, %20, 1, 1, 1, 1;"
                     : "+r"(d[0]), "+r"(d[1]), "+r"(d[2]), "+r"(d[3]), "+r"(d[4]), "+r"(d[5]), "+r"(d[6]), "+r"(d[7]), "+r"(d[8]), "+r"(d[9]), "+r"(d[10]), "+r"(d[11]), "+r"(d[12]), "+r"(d[13]), "+r"(d[14]), "+r"(d[15])
                     : "r"(a0), "r"(a1), "r"(a2), "r"(a3), "l"(desc) : "memory");
    }
    static __device__ __forceinline__ void first(uint32_t* d, uint32_t a0, uint32_t a1, uint32_t a2, uint32_t a3, uint64_t desc) {
        asm volatile("wgmma.mma_async.sync.aligned.m64n64k16.f16.f16.f16 {%0,%1,%2,%3,%4,%5,%6,%7,%8,%9,%10,%11,%12,%13,%14,%15}, "
                     "{%16,%17,%18,%19}, %20, 0, 1, 1, 1;"
                     : "=r"(d[0]), "=r"(d[1]), "=r"(d[2]), "=r"(d[3]), "=r"(d[4]), "=r"(d[5]), "=r"(d[6]), "=r"(d[7]), "=r"(d[8]), "=r"(d[9]), "=r"(d[10]), "=r"(d[11]), "=r"(d[12]), "=r"(d[13]), "=r"(d[14]), "=r"(d[15])
                     : "r"(a0), "r"(a1), "r"(a2), "r"(a3), "l"(desc) : "memory");
    }
};
template <> struct WH<96> {
    static __device__ __forceinline__ void acc(uint32_t* d, uint32_t a0, uint32_t a1, uint32_t a2, uint32_t a3, uint64_t desc) {
        asm volatile("wgmma.mma_async.sync.aligned.m64n96k16.f16.f16.f16 {%0,%1,%2,%3,%4,%5,%6,%7,%8,%9,%10,%11,%12,%13,%14,%15,%16,%17,%18,%19,%20,%21,%22,%23}, "
                     "{%24,%25,%26,%27}, %28, 1, 1, 1, 1;"
                     : "+r"(d[0]), "+r"(d[1]), "+r"(d[2]), "+r"(d[3]), "+r"(d[4]), "+r"(d[5]), "+r"(d[6]), "+r"(d[7]), "+r"(d[8]), "+r"(d[9]), "+r"(d[10]), "+r"(d[11]), "+r"(d[12]), "+r"(d[13]), "+r"(d[14]), "+r"(d[15]), "+r"(d[16]), "+r"(d[17]), "+r"(d[18]), "+r"(d[19]), "+r"(d[20]), "+r"(d[21]), "+r"(d[22]), "+r"(d[23])
                     : "r"(a0), "r"(a1), "r"(a2), "r"(a3), "l"(desc) : "memory");
    }
    static __device__ __forceinline__ void first(uint32_t* d, uint32_t a0, uint32_t a1, uint32_t a2, uint32_t a3, uint64_t desc) {
        asm volatile("wgmma.mma_async.sync.aligned.m64n96k16.f16.f16.f16 {%0,%1,%2,%3,%4,%5,%6,%7,%8,%9,%10,%11,%12,%13,%14,%15,%16,%17,%18,%19,%20,%21,%22,%23}, "
                     "{%24,%25,%26,%27}, %28, 0, 1, 1, 1;"
                     : "=r"(d[0]), "=r"(d[1]), "=r"(d[2]), "=r"(d[3]), "=r"(d[4]), "=r"(d[5]), "=r"(d[6]), "=r"(d[7]), "=r"(d[8]), "=r"(d[9]), "=r"(d[10]), "=r"(d[11]), "=r"(d[12]), "=r"(d[13]), "=r"(d[14]), "=r"(d[15]), "=r"(d[16]), "=r"(d[17]), "=r"(d[18]), "=r"(d[19]), "=r"(d[20]), "=r"(d[21]), "=r"(d[22]), "=r"(d[23])
                     : "r"(a0), "r"(a1), "r"(a2), "r"(a3), "l"(desc) : "memory");
    }
};

__device__ __forceinline__ void wgmma_stat(float (&d)[4], const uint32_t (&a)[4], uint64_t desc) {
    asm volatile("wgmma.mma_async.sync.aligned.m64n8k16.f32.bf16.bf16 {%0,%1,%2,%3}, {%4,%5,%6,%7}, %8, 0, 1, 1, 1;"
                 : "=f"(d[0]), "=f"(d[1]), "=f"(d[2]), "=f"(d[3]) : "r"(a[0]), "r"(a[1]), "r"(a[2]), "r"(a[3]), "l"(desc) : "memory");
}

__device__ __forceinline__ uint64_t make_desc(uint32_t addr, uint32_t lbo, uint32_t sbo) {
    return (uint64_t)((addr & 0x3FFFF) >> 4) | ((uint64_t)(lbo >> 4) << 16) | ((uint64_t)(sbo >> 4) << 32);
}

#define SCHED_FENCE() asm volatile("{\n\t.reg .pred p;\n\tsetp.ne.u32 p, %0, 0;\n\t@p exit;\n\t}" ::"r"(zero) : "memory")

__global__ void __launch_bounds__(NUM_THREADS, 1)
convnext_fused_kernel(const __grid_constant__ CUtensorMap xmap, const __grid_constant__ CUtensorMap w1map,
                      const __nv_bfloat16* __restrict__ dw, const __nv_bfloat16* __restrict__ w1,
                      const __nv_bfloat16* __restrict__ b1, const __nv_bfloat16* __restrict__ w2,
                      const __nv_bfloat16* __restrict__ b2, const __nv_bfloat16* __restrict__ gamma,
                      __nv_bfloat16* __restrict__ out, uint32_t zero) {
    extern __shared__ __align__(1024) uint8_t smem[];
    const uint32_t sbase = smem_u32(smem);
    const int tid = threadIdx.x;
    const int warp = __shfl_sync(0xffffffffu, tid >> 5, 0);
    const int lane = tid & 31;
    const int wg = warp >> 2, wr = warp & 3;
    const uint32_t bars = sbase + OFF_BAR;
    const int strip = blockIdx.x % NUM_STRIPS;
    const int band = blockIdx.x / NUM_STRIPS;
    const int dir = (band & 1) ? 1 : -1;
    const int ys = (band & 1) ? band * ROWS_PER_CTA - 1 : (band + 1) * ROWS_PER_CTA;

    auto load_row = [&](int j) {
        const uint32_t bar = bars + 8 * (BAR_ROW_FULL + (j & 3));
        const uint32_t dst = sbase + OFF_ROW + (j & 3) * ROW_BYTES;
        mbar_expect_tx(bar, 2 * HALF_BYTES);
        tma_load_3d(dst, &xmap, bar, 0, strip * STRIP_W - 1, ys + dir * j);
        tma_load_3d(dst + HALF_BOX, &xmap, bar, 0, strip * STRIP_W + 30, ys + dir * j);
    };
    auto load_w2 = [&](int s) {
        mbar_expect_tx(bars + 8 * (BAR_W2 + s), CH * HID / 2);
        bulk_load(sbase + OFF_W2 + s * (CH * HID / 2), w2 + s * (CH * HID / 4), CH * HID / 2, bars + 8 * (BAR_W2 + s));
    };
    if (warp == 11) {
        if (elect_one()) {
            asm volatile("prefetch.tensormap [%0];" ::"l"(reinterpret_cast<uint64_t>(&w1map)) : "memory");
#pragma unroll
            for (int s = 0; s < NUM_BARS; ++s)
                if (s < BAR_DONE || (s >= BAR_W1 && s <= BAR_DW)) mbar_init(bars + 8 * s, 1);
            asm volatile("fence.mbarrier_init.release.cluster;" ::: "memory");
        }
        __syncwarp();
        asm volatile("bar.arrive 2, %0;" ::"n"(NUM_THREADS) : "memory");
        if (elect_one()) {
#pragma unroll 1
            for (int s = 0; s < NCHUNK; ++s) {
                mbar_expect_tx(bars + 8 * (BAR_W1 + s), CH * NCH * 2);
                tma_load_2d(sbase + OFF_W1 + s * (CH * NCH * 2), &w1map, bars + 8 * (BAR_W1 + s), s * NCH, 0);
            }
            mbar_expect_tx(bars + 8 * BAR_DW, 9 * CH * 2);
            bulk_load(sbase + OFF_DW, dw, 9 * CH * 2, bars + 8 * BAR_DW);
            load_row(0);
            load_row(1);
            load_row(2);
#pragma unroll 1
            for (int s = 0; s < 4; ++s) load_w2(s);
            load_row(3);
        }
        __syncwarp();
        asm volatile("bar.sync 3, 64;" ::: "memory");
    } else if (warp == 9) {
        if (elect_one()) {
#pragma unroll
            for (int s = BAR_DONE; s < BAR_W1; ++s) mbar_init(bars + 8 * s, s < BAR_PRIME ? 8 : 4);
            mbar_init(bars + 8 * BAR_W1RDY, 4 * NMLP);
            mbar_init(bars + 8 * BAR_W2RDY, 8);
            asm volatile("mbarrier.arrive.shared::cta.b64 _, [%0], 4;" ::"r"(bars + 8 * BAR_DONE) : "memory");
        }
        __syncwarp();
        asm volatile("bar.arrive 3, 64;" ::: "memory");
    } else if (warp == 10) {
        if (elect_one()) asm volatile("prefetch.tensormap [%0];" ::"l"(reinterpret_cast<uint64_t>(&xmap)) : "memory");
    }

    if (wg == NMLP) {
        asm volatile("setmaxnreg.dec.sync.aligned.u32 128;");
        asm volatile("bar.sync 2, %0;" ::"n"(NUM_THREADS) : "memory");
        uint32_t w[3][3][3];
        {
            mbar_wait(bars + 8 * BAR_DW, 0);
            const uint32_t wp = sbase + OFF_DW + 48 * ((wr + (lane >> 2)) & 3) + 4 * (lane & 3) + 3 * (CH * 2);
#pragma unroll
            for (int s = 0; s < 3; ++s)
#pragma unroll
                for (int t = 0; t < 9; ++t) w[t / 3][t % 3][s] = lds32(wp + (t / 3 - 1) * dir * 3 * (CH * 2) + (t % 3) * (CH * 2) + s * 16);
        }
        const int ga = lane & 7, ja = lane >> 3;
        const uint32_t ip = sbase + OFF_ROW + (uint32_t)((ga >> 2) * HALF_OFF + (8 * (ga & 3) + ja) * (CH * 2) + 48 * ((wr + ga) & 3));
        const uint32_t op = sbase + OFF_A + (uint32_t)((ga >> 2) * A_HALF + (8 * (ga & 3) + ja) * A_PITCH + 48 * ((wr + ga) & 3));
        static_assert(NROW == 4 && NA == 2, "ring arithmetic");
        uint32_t P[2][3][8], f[10], c[8];
        auto load_window = [&](uint32_t a) {
            ldsm_x4(a, f[0], f[1], f[2], f[3]);
            ldsm_x4(a + 4 * (CH * 2), f[4], f[5], f[6], f[7]);
            ldsm_x2(a + 8 * (CH * 2), f[8], f[9]);
        };
        auto feed = [&](int e, int s, int i) {
#pragma unroll
            for (int o = i - 2; o <= i; ++o) {
                if (o < 0 || o > 7) continue;
                const int jx = i - o;
                if (jx == 0) {
                    asm volatile("fma.rn.bf16x2 %0, %3, %4, %1;\n\tfma.rn.bf16x2 %2, %3, %5, %2;\n\tmul.rn.bf16x2 %1, %3, %6;"
                                 : "=&r"(c[o]), "+r"(P[e][s][o]), "+r"(P[e ^ 1][s][o])
                                 : "r"(f[i]), "r"(w[2][0][s]), "r"(w[1][0][s]), "r"(w[0][0][s]));
                } else {
                    asm volatile("fma.rn.bf16x2 %0, %3, %4, %0;\n\tfma.rn.bf16x2 %2, %3, %5, %2;\n\tfma.rn.bf16x2 %1, %3, %6, %1;"
                                 : "+r"(c[o]), "+r"(P[e][s][o]), "+r"(P[e ^ 1][s][o])
                                 : "r"(f[i]), "r"(w[2][jx][s]), "r"(w[1][jx][s]), "r"(w[0][jx][s]));
                }
            }
        };
        __nv_bfloat16* xo = out + ((ys + dir) * IMG_W + strip * STRIP_W + wr * 16) * CH;
        const uint32_t xs = sbase + OFF_ROW + (wr >> 1) * HALF_OFF + ((wr & 1) * 16 + 1) * (CH * 2);
        mbar_wait(bars + 8 * BAR_ROW_FULL, 0);
#pragma unroll
        for (int r = 0; r < 2; ++r) {
            if (r == 1) {
                mbar_wait(bars + 8 * (BAR_ROW_FULL + 1), 0);
                if (elect_one()) bulk_store(xo, xs + ROW_BYTES, 16 * CH * 2);
                bulk_commit();
            }
#pragma unroll
            for (int s = 0; s < 3; ++s) {
                load_window(ip + r * ROW_BYTES + s * 16);
#pragma unroll
                for (int o = 0; o < 8; ++o) {
                    if (r == 1) P[0][s][o] = hfma2_bf16(f[o + 2], w[1][2][s], hfma2_bf16(f[o + 1], w[1][1][s], hfma2_bf16(f[o], w[1][0][s], P[0][s][o])));
                    P[r][s][o] = hfma2_bf16(f[o + 2], w[0][2][s], hfma2_bf16(f[o + 1], w[0][1][s], hmul2_bf16(f[o], w[0][0][s])));
                }
            }
        }
        __syncwarp();
        if (elect_one()) mbar_arrive(bars + 8 * BAR_PRIME);
        mbar_wait(bars + 8 * (BAR_ROW_FULL + 2), 0);
        load_window(ip + 2 * ROW_BYTES);
        uint32_t dbar = bars + 8 * BAR_DONE;
#pragma unroll 1
        for (int m = 0; m < ROWS_PER_CTA / 4; ++m) {
            const bool last = m + 1 == ROWS_PER_CTA / 4;
#pragma unroll
            for (int u = 0; u < 4; ++u) {
                const int j = 4 * m + u + 2;
                const int rs = (u + 2) & 3, ns = (u + 3) & 3;
                const uint32_t ebar = bars + 8 * (BAR_A_EMPTY + (u & 1)), rbar = bars + 8 * (BAR_ROW_FULL + ns);
                const uint32_t eph = ((u >> 1) & 1) ^ 1, rph = (m + (u >= 1)) & 1;
                xo += dir * IMG_W * CH;
                if (!(u == 3 && last)) {
                    if (elect_one()) bulk_store(xo, xs + rs * ROW_BYTES, 16 * CH * 2);
                }
                bulk_commit();
                bool ok = mbar_test(ebar, eph);
#pragma unroll
                for (int s = 0; s < 3; ++s) {
                    if (s == 2) ok = mbar_test(rbar, rph) || (u == 3 && last);
                    feed(u & 1, s, 0); feed(u & 1, s, 1); feed(u & 1, s, 2); feed(u & 1, s, 3);
                    if (s == 0) {
                        if (!ok) mbar_wait(ebar, eph);
                    }
                    const uint32_t nx = ip + (s == 2 ? ns : rs) * ROW_BYTES + ((s + 1) % 3) * 16;
                    const uint32_t ox = op + (u & 1) * A_BYTES + s * 16;
                    if (s < 2 || ok) ldsm_x4(nx, f[0], f[1], f[2], f[3]);
                    SCHED_FENCE();
                    feed(u & 1, s, 4); feed(u & 1, s, 5);
                    stsm_x4(ox, c[0], c[1], c[2], c[3]);
                    feed(u & 1, s, 6); feed(u & 1, s, 7);
                    ldsm_x4(nx + 4 * (CH * 2), f[4], f[5], f[6], f[7]);
                    SCHED_FENCE();
                    feed(u & 1, s, 8); feed(u & 1, s, 9);
                    stsm_x4(ox + 4 * A_PITCH, c[4], c[5], c[6], c[7]);
                    ldsm_x2(nx + 8 * (CH * 2), f[8], f[9]);
                    SCHED_FENCE();
                }
                bulk_wait<1>();
                __syncwarp();
                const bool el = elect_one();
                if (el) mbar_arrive(dbar);
                bulk_wait_read<0>();
                if (el) mbar_arrive(bars + 8 * (BAR_FREE + (u & 1)));
                dbar = dbar == bars + 8 * (BAR_DONE + NMLP - 1) ? bars + 8 * BAR_DONE : dbar + 8;
                if ((wr == u && !last) || (u == 0 && m == 0 && wr == 1)) {
                    mbar_wait(bars + 8 * (BAR_FREE + (u & 1)), (u >> 1) & 1);
                    if (elect_one()) load_row(u == 0 ? j + 4 - wr : j + 4);
                }
                if (!ok) {
                    mbar_wait(rbar, rph);
                    load_window(ip + ns * ROW_BYTES);
                }
            }
        }
    } else {
        const int g = lane >> 2, q = lane & 3;
        const uint4 r95 = __ldg(reinterpret_cast<const uint4*>(w1 + 95 * HID + (warp >> 1) * NCH + (lane & 7) * 8));
        const uint4 bb = __ldg(reinterpret_cast<const uint4*>(b1 + (warp >> 1) * NCH + (lane & 7) * 8));
        uint4 gm[3];
#pragma unroll
        for (int jj = 0; jj < 3; ++jj) gm[jj] = __ldg(reinterpret_cast<const uint4*>(gamma + jj * 32 + q * 8));
        uint32_t b2v = 0, g2v = 0;
        if (tid >= 128 && tid < 128 + CH / 2) {
            b2v = __ldg(reinterpret_cast<const uint32_t*>(b2) + tid - 128);
            g2v = __ldg(reinterpret_cast<const uint32_t*>(gamma) + tid - 128);
        }
        auto transform_w2 = [&](int s, int pass) {
            const uint32_t w2b = sbase + OFF_W2 + (warp - 4) * 6 * (8 * CH * 2);
            const float up = __uint_as_float((uint32_t)(127 + s) << 23), sc = up * GELU_INV2A;
            uint32_t gh[12];
#pragma unroll
            for (int e = 0; e < 12; ++e) {
                const uint32_t gv = (e & 3) == 0 ? gm[e / 4].x : (e & 3) == 1 ? gm[e / 4].y : (e & 3) == 2 ? gm[e / 4].z : gm[e / 4].w;
                gh[e] = pack_bf16(bf_lo(gv) * sc * 0x1p-112f, bf_hi(gv) * sc * 0x1p-112f);
            }
            if (tid < 128 + CH / 2) {
                const uint32_t v2 = pack_f16(bf_lo(b2v) * bf_lo(g2v) * up, bf_hi(b2v) * bf_hi(g2v) * up);
                const uint32_t a = sbase + OFF_B2I + (((tid >> 4) & 3) * 2 + ((tid >> 1) & 1)) * 128 + ((tid >> 2) & 3) * 16 + (tid & 1) * 8;
                sts32(a, v2); sts32(a + 4, v2);
                sts32(a + 64, 0); sts32(a + 68, 0);
            }
            mbar_wait(bars + 8 * (BAR_W2 + (warp >> 1) - 2), pass);
            uint4 v[3];
#pragma unroll
            for (int jj = 0; jj < 3; ++jj) v[jj] = lds128(w2b + g * (CH * 2) + jj * 64 + q * 16);
            uint32_t mu = 0, ms = 0;
#pragma unroll 1
            for (int i = 0; i < 6; ++i) {
                uint32_t o[12];
#pragma unroll
                for (int jj = 0; jj < 3; ++jj) {
                    mu = __vmaxu2(__vmaxu2(mu, v[jj].x), v[jj].y); mu = __vmaxu2(__vmaxu2(mu, v[jj].z), v[jj].w);
                    ms = __vmaxs2(__vmaxs2(ms, v[jj].x), v[jj].y); ms = __vmaxs2(__vmaxs2(ms, v[jj].z), v[jj].w);
                    o[jj * 4 + 0] = hmul2_bf16(v[jj].x, gh[jj * 4 + 0]);
                    o[jj * 4 + 1] = hmul2_bf16(v[jj].y, gh[jj * 4 + 1]);
                    o[jj * 4 + 2] = hmul2_bf16(v[jj].z, gh[jj * 4 + 2]);
                    o[jj * 4 + 3] = hmul2_bf16(v[jj].w, gh[jj * 4 + 3]);
                    if (i < 5) v[jj] = lds128(w2b + (i + 1) * (8 * CH * 2) + g * (CH * 2) + jj * 64 + q * 16);
                }
                __syncwarp();
#pragma unroll
                for (int e = 0; e < 12; ++e) o[e] = bf2_to_h2(o[e]);
#pragma unroll
                for (int jj = 0; jj < 3; ++jj)
                    stsm_x4(w2b + i * (8 * CH * 2) + jj * 512 + lane * 16, o[jj * 4], o[jj * 4 + 1], o[jj * 4 + 2], o[jj * 4 + 3]);
            }
            mu = __vmaxu2(mu & 0x7fff7fffu, ms);
            return __reduce_max_sync(0xffffffffu, max(mu & 0xffffu, mu >> 16));
        };
        if (warp != 11) asm volatile("bar.sync 2, %0;" ::"n"(NUM_THREADS) : "memory");
        asm volatile("setmaxnreg.inc.sync.aligned.u32 128;");
        {
            const int box = warp >> 1, cc = lane & 7, k0 = (warp & 1) * 48 + (lane >> 3);
            constexpr uint32_t DN = 0x07800780u;
            if (tid < 16) {
                const uint32_t v = tid < 8 ? 0x3F80u : 0x3F800000u;
                sts128(sbase + OFF_SEL + tid * 16, v, v, v, v);
            }
            const uint32_t m[4] = {hmul2_bf16(r95.x, DN | 0x80008000u), hmul2_bf16(r95.y, DN | 0x80008000u),
                                   hmul2_bf16(r95.z, DN | 0x80008000u), hmul2_bf16(r95.w, DN | 0x80008000u)};
            const uint32_t tb[4] = {scale2h(bb.x, GELU_A), scale2h(bb.y, GELU_A), scale2h(bb.z, GELU_A), scale2h(bb.w, GELU_A)};
            uint32_t mx = absmax2(absmax2(absmax2(absmax2(0, hmul2_bf16(bb.x, DN)), hmul2_bf16(bb.y, DN)), hmul2_bf16(bb.z, DN)), hmul2_bf16(bb.w, DN));
            uint32_t mg = 0;
#pragma unroll
            for (int jj = 0; jj < 3; ++jj) mg = absmax2(absmax2(absmax2(absmax2(mg, gm[jj].x), gm[jj].y), gm[jj].z), gm[jj].w);
            mg = __reduce_max_sync(0xffffffffu, max(mg & 0xffffu, mg >> 16));
            if (warp == 4 || warp == 5) {
                const uint32_t mb = __reduce_max_sync(0xffffffffu, max(b2v & 0x7fffu, (b2v >> 16) & 0x7fffu));
                if (lane == 0) sts32(sbase + OFF_MAX + 32 + warp * 4, mb);
            }
            const uint32_t wb = sbase + OFF_W1 + box * (CH * NCH * 2);
            const uint32_t wa[2] = {wb + k0 * 128 + ((cc ^ (k0 & 7)) << 4), wb + (k0 + 4) * 128 + ((cc ^ ((k0 + 4) & 7)) << 4)};
            mbar_wait(bars + 8 * (BAR_W1 + box), 0);
            uint4 u[2] = {lds128(wa[0]), lds128(wa[1])};
#pragma unroll 1
            for (int i = 0; i < 6; ++i) {
                uint32_t t[2][4];
#pragma unroll
                for (int e = 0; e < 2; ++e) {
                    t[e][0] = hfma2_bf16(u[e].x, DN, m[0]); t[e][1] = hfma2_bf16(u[e].y, DN, m[1]);
                    t[e][2] = hfma2_bf16(u[e].z, DN, m[2]); t[e][3] = hfma2_bf16(u[e].w, DN, m[3]);
                    if (i < 5) u[e] = lds128(wa[e] + (i + 1) * 1024);
#pragma unroll
                    for (int x = 0; x < 4; ++x) {
                        mx = absmax2(mx, t[e][x]);
                        t[e][x] = bf2_to_h2(t[e][x]);
                    }
                }
                sts128(wa[0] + i * 1024, t[0][0], t[0][1], t[0][2], t[0][3]);
                sts128(wa[1] + i * 1024, t[1][0], t[1][1], t[1][2], t[1][3]);
            }
            if (k0 + 44 == 95) sts128(wa[1] + 5 * 1024, tb[0], tb[1], tb[2], tb[3]);
            const uint32_t m1w = __reduce_max_sync(0xffffffffu, max(mx & 0xffffu, mx >> 16));
            if (lane == 0) sts32(sbase + OFF_MAX + warp * 4, m1w << 16);
            asm volatile("fence.proxy.async.shared::cta;" ::: "memory");
            __syncwarp();
            if (elect_one()) mbar_arrive(bars + 8 * BAR_W1RDY);
            if (wg > 0) {
                const uint32_t m2w = transform_w2(0, 0);
                if (lane == 0) sts32(sbase + OFF_MAX + warp * 4, m2w | (m1w << 16));
                asm volatile("fence.proxy.async.shared::cta;" ::: "memory");
                mbar_wait(bars + 8 * BAR_W1RDY, 0);
                asm volatile("bar.sync 1, 256;" ::: "memory");
                const uint32_t mm = lane < 14 ? lds32(sbase + OFF_MAX + lane * 4) : 0;
                const uint32_t m1 = __reduce_max_sync(0xffffffffu, lane < 12 ? mm >> 16 : 0);
                const uint32_t m2 = __reduce_max_sync(0xffffffffu, lane < 12 ? mm & 0xffffu : 0), mb = __reduce_max_sync(0xffffffffu, lane < 12 ? 0 : mm);
                const int e1 = max((int)(m1 >> 7), 1) - 14, eg = (int)(mg >> 7) - 126, ew = (int)(m2 >> 7) - 126;
                const int e2 = ew + eg + 1, eb = (int)(mb >> 7) - 126 + eg;
                int s = min(min(-1 - e1 - e2, 14 - eb), 14 - e2);
                if (s >= 0 && s <= 12 && e2 >= -9 && eg >= -9) s = 0;
                s = min(max(s, -120), min(120, 120 - eg));
                if (s != 0) {
                    if ((warp & 1) == 0 && elect_one()) load_w2((warp >> 1) - 2);
                    transform_w2(s, 1);
                    asm volatile("fence.proxy.async.shared::cta;" ::: "memory");
                }
                if (tid == 128) sts32(sbase + OFF_MAX + 64, (uint32_t)(127 - s) * 0x00800080u);
                __syncwarp();
                if (elect_one()) mbar_arrive(bars + 8 * BAR_W2RDY);
            } else if (wr == 0) {
                mbar_wait(bars + 8 * BAR_PRIME, 0);
                if (elect_one()) load_row(4);
            }
        }
        const uint64_t descW1 = make_desc(sbase + OFF_W1, CH * NCH * 2, 1024) | (1ull << 62);
        const uint64_t descW2 = make_desc(sbase + OFF_W2, (CH / 8) * 128, 128);
        const uint64_t descS = make_desc(sbase + OFF_SEL, 128, 128);
        uint32_t la = sbase + OFF_A + (wg & 1) * A_BYTES + wr * 16 * A_PITCH + (wr >> 1) * 64 +
                      (uint32_t)(((lane & 7) + ((lane >> 3) & 1) * 8) * A_PITCH + (lane >> 4) * 16);

        uint32_t acc2[24];
        uint32_t h[2][NCH / 4];
        uint32_t a1[6][4];
        uint32_t pp[4];
        float st[4];

        auto load_a = [&]() {
#pragma unroll
            for (int kb = 0; kb < 6; ++kb) ldsm_x4(la + kb * 32, a1[kb][0], a1[kb][1], a1[kb][2], a1[kb][3]);
        };
        auto partial_a = [&](int i) {
            uint32_t s = hadd2_bf16(hadd2_bf16(hadd2_bf16(a1[0][i], a1[1][i]), hadd2_bf16(a1[2][i], a1[3][i])), hadd2_bf16(a1[4][i], a1[5][i]));
            uint32_t v = hmul2_bf16(a1[0][i], a1[0][i]);
#pragma unroll
            for (int kb = 1; kb < 6; ++kb) v = hfma2_bf16(a1[kb][i], a1[kb][i], v);
            if (i >= 2) { s = hadd2_bf16(s, pp[i & 1]); v = hadd2_bf16(v, pp[2 + (i & 1)]); }
            asm volatile("" : "+r"(s), "+r"(v));
            pp[i & 1] = s; pp[2 + (i & 1)] = v;
        };
        uint32_t sel95 = q == 3 ? 0x7610 : 0x3210;
        asm volatile("" : "+r"(sel95));
        auto norm_a = [&]() {
            constexpr float K = GELU_A * 0x1p-112f, SQ = 9.797958971132712f;
            float m0 = st[0] * (-1.f / CH), m1 = st[2] * (-1.f / CH);
            float r0, r1;
            asm("rsqrt.approx.ftz.f32 %0, %1;" : "=f"(r0) : "f"(fmaxf(fmaf(m0, st[0], st[1]), 0.f) + CH * 1e-5f));
            asm("rsqrt.approx.ftz.f32 %0, %1;" : "=f"(r1) : "f"(fmaxf(fmaf(m1, st[2], st[3]), 0.f) + CH * 1e-5f));
            const uint32_t rp = pack_bf16(r0 * (K * SQ), r1 * (K * SQ));
            const float o0 = m0 * bf_lo(rp), o1 = m1 * bf_hi(rp);
            const uint32_t op = pack_bf16(o0, o1);
            const bool easy = (fmaxf(fabsf(o0), fabsf(o1)) < 0.5f * K) & (fminf(r0, r1) > 0x1p-12f);
            if (__all_sync(0xffffffffu, easy)) {
#pragma unroll
                for (int kb = 0; kb < 6; ++kb)
#pragma unroll
                    for (int i = 0; i < 4; ++i)
                        a1[kb][i] = bf2_to_h2((i & 1) ? hfma2_bf16_bcast<true>(a1[kb][i], rp, op) : hfma2_bf16_bcast<false>(a1[kb][i], rp, op));
            } else {
                float s0[2] = {0.f, 0.f}, s1[2] = {0.f, 0.f}, v0[2] = {0.f, 0.f}, v1[2] = {0.f, 0.f};
#pragma unroll
                for (int kb = 0; kb < 6; ++kb)
#pragma unroll
                    for (int i = 0; i < 2; ++i) {
                        float a = bf_lo(a1[kb][2 * i]), b = bf_hi(a1[kb][2 * i]);
                        s0[0] += a; v0[0] = fmaf(a, a, v0[0]); s0[1] += b; v0[1] = fmaf(b, b, v0[1]);
                        a = bf_lo(a1[kb][2 * i + 1]); b = bf_hi(a1[kb][2 * i + 1]);
                        s1[0] += a; v1[0] = fmaf(a, a, v1[0]); s1[1] += b; v1[1] = fmaf(b, b, v1[1]);
                    }
                float sa = s0[0] + s0[1], sb = s1[0] + s1[1], va = v0[0] + v0[1], vb = v1[0] + v1[1];
                sa += __shfl_xor_sync(0xffffffffu, sa, 1); sb += __shfl_xor_sync(0xffffffffu, sb, 1);
                va += __shfl_xor_sync(0xffffffffu, va, 1); vb += __shfl_xor_sync(0xffffffffu, vb, 1);
                sa += __shfl_xor_sync(0xffffffffu, sa, 2); sb += __shfl_xor_sync(0xffffffffu, sb, 2);
                va += __shfl_xor_sync(0xffffffffu, va, 2); vb += __shfl_xor_sync(0xffffffffu, vb, 2);
                m0 = sa * (1.f / CH); m1 = sb * (1.f / CH);
                asm("rsqrt.approx.ftz.f32 %0, %1;" : "=f"(r0) : "f"(fmaxf(fmaf(-m0, m0, va * (1.f / CH)), 0.f) + 1e-5f));
                asm("rsqrt.approx.ftz.f32 %0, %1;" : "=f"(r1) : "f"(fmaxf(fmaf(-m1, m1, vb * (1.f / CH)), 0.f) + 1e-5f));
                r0 *= GELU_A; r1 *= GELU_A;
                const float p0 = -m0 * r0, p1 = -m1 * r1;
#pragma unroll
                for (int kb = 0; kb < 6; ++kb)
#pragma unroll
                    for (int i = 0; i < 4; ++i) {
                        const float r = (i & 1) ? r1 : r0, o = (i & 1) ? p1 : p0;
                        a1[kb][i] = pack_f16(fmaf(bf_lo(a1[kb][i]), r, o), fmaf(bf_hi(a1[kb][i]), r, o));
                    }
            }
            a1[5][2] = __byte_perm(a1[5][2], 0x3C000000u, sel95);
            a1[5][3] = __byte_perm(a1[5][3], 0x3C000000u, sel95);
        };
        auto gemm1 = [&](int c, int k0, int k1) {
#pragma unroll
            for (int kk = k0; kk < k1; ++kk) {
                if (kk == 0) WH<NCH>::first(h[c & 1], a1[0][0], a1[0][1], a1[0][2], a1[0][3], descW1 + (uint64_t)(c * 768));
                else WH<NCH>::acc(h[c & 1], a1[kk][0], a1[kk][1], a1[kk][2], a1[kk][3], descW1 + (uint64_t)(c * 768 + kk * 128));
            }
        };
        auto gemm2 = [&](int c, int k0, int k1) {
#pragma unroll
            for (int kk = k0; kk < k1; ++kk)
                WH<96>::acc(acc2, h[c & 1][kk * 4], h[c & 1][kk * 4 + 1], h[c & 1][kk * 4 + 2], h[c & 1][kk * 4 + 3],
                            descW2 + (uint64_t)(((c * (NCH / 8) + 2 * kk) * (CH / 8)) * 8));
        };
        uint32_t b2a = sbase + OFF_B2I + q * 16;
        asm volatile("" : "+r"(b2a));

        mbar_wait(bars + 8 * BAR_W1RDY, 0);
        static_assert((OFF_BAR + 8 * BAR_A_EMPTY) % 16 == 0 && (NMLP & 1), "the conv-tile slot alternates");
        const uint32_t nbar = bars + 8 * (BAR_DONE + wg), tbar = bars + 8 * (BAR_DONE + (wg + 1) % NMLP);
        uint32_t ebar = bars + 8 * (BAR_A_EMPTY + (wg & 1)), nph = 0;
        const uint32_t lsum = 2 * la + ((wg & 1) ? -A_BYTES : A_BYTES);
        mbar_wait(nbar, 0);
        load_a();
#pragma unroll
        for (int i = 0; i < 4; ++i) partial_a(i);
        wg_fence();
        wgmma_stat(st, pp, descS);
        wg_commit();
        __syncwarp();
        if (elect_one()) {
            mbar_arrive(ebar);
            mbar_arrive(tbar);
        }
        wg_wait<0>();
        fence_regs(st);
        norm_a();
        wg_fence();
        gemm1(0, 0, 6);
        wg_commit();
        mbar_wait(bars + 8 * BAR_W2RDY, 0);
        const uint32_t oscale = lds32(sbase + OFF_MAX + 64);
        uint32_t y[24];
#pragma unroll
        for (int m = 0; m < 6; ++m) {
            const uint4 v = lds128(b2a + m * 128);
            y[4 * m] = y[4 * m + 1] = hmul2_bf16(h2_to_bf2(v.x), oscale);
            y[4 * m + 2] = y[4 * m + 3] = hmul2_bf16(h2_to_bf2(v.z), oscale);
        }
        wg_wait<0>();
        b2a += 64;
        __nv_bfloat16* optr = out + ((ys + dir * (wg + 1)) * IMG_W + strip * STRIP_W + wr * 16 + g) * CH + q * 8;
        auto red_y = [&](int i, uint64_t pol) {
            const int jj = i / 2, hrow = i % 2;
            red_add_bf16x8(optr + hrow * 8 * CH + jj * 32, y[jj * 8 + hrow], y[jj * 8 + hrow + 2], y[jj * 8 + hrow + 4], y[jj * 8 + hrow + 6], pol);
        };
#pragma unroll 1
        for (int t = wg;; t += NMLP) {
            const bool more = t + NMLP < ROWS_PER_CTA;
            bool ready = true;
            const uint64_t rpol = t != wg ? policy_evict_first() : policy_evict_normal();
            SCHED_FENCE();
            constexpr int P = NCH / 4, NP = HID / 4;
            uint32_t zz[2];
            uint16_t t0[LAG], t1[LAG];
#pragma unroll
            for (int G = 0; G <= NP + LAG; ++G) {
                const int ca = G / P, gp = G % P;
                if (G == TESTPOS) ready = mbar_test(nbar, nph) || !more;
                if (G == NP - P && !ready) mbar_wait(nbar, nph);
                if (gp == 0 && ca >= 1 && G < NP) { wg_wait<1>(); fence_regs(h[ca & 1]); }
                if (G == NP - P) load_a();
                if (ca + 1 < NCHUNK && gp == (ca == 0 ? 1 : G1PA)) {
                    if (ca > 0) wg_wait<0>();
                    wg_fence();
                    gemm1(ca + 1, 0, 3);
                }
                if (ca + 1 < NCHUNK && gp == (ca == 0 ? 3 : G1PB)) {
                    wg_fence();
                    gemm1(ca + 1, 3, 6);
                    wg_commit();
                }
                if (ca < NCHUNK && gp == G2PA) {
                    fence_regs(h[ca & 1]);
                    wg_fence();
                    if (G == STATPOS) wgmma_stat(st, pp, descS);
                    gemm2(ca, 0, 2);
                    wg_commit();
                }
                if (ca >= 1 && gp == G2PB - P) {
                    fence_regs(h[(ca - 1) & 1]);
                    wg_fence();
                    gemm2(ca - 1, 2, 4);
                    wg_commit();
                }
                if (G == INITPOS) {
#pragma unroll
                    for (int m = 0; m < 6; ++m) {
                        const uint4 v = lds128(b2a + m * 128);
                        acc2[4 * m] = v.x; acc2[4 * m + 1] = v.y; acc2[4 * m + 2] = v.z; acc2[4 * m + 3] = v.w;
                    }
                }
                if (G == RELPOS) {
                    __syncwarp();
                    if (elect_one() & more) mbar_arrive(ebar);
                }
                if (G >= REDPOS && G < REDPOS + 6 * REDSTEP && (G - REDPOS) % REDSTEP == 0) red_y((G - REDPOS) / REDSTEP, rpol);
                if (G == 4 * P + 4) {
                    asm volatile("sub.u32 %0, %1, %0;" : "+r"(la) : "r"(lsum));
                    asm volatile("and.b32 %0, %0, 0xffffffbf;" : "+r"(b2a));
                    ebar ^= 8;
                    nph ^= 1;
                    asm volatile("add.u64 %0, %0, %1;" : "+l"(optr) : "l"(t == wg ? 0ll : (long long)dir * (NMLP * IMG_W * CH * 2)));
                }
                if (G >= STATPOS - 4 && G < STATPOS) partial_a(G - (STATPOS - 4));
                int e = G - LAG;
                if (e >= 0 && e < NP) {
                    uint32_t& v = h[(e / P) & 1][e % P];
                    uint32_t o;
                    asm volatile("{\n\t.reg .b32 t;\n\tmov.b32 t, {%2, %3};\n\tfma.rn.f16x2 %0, %1, t, %1;\n\t}"
                                 : "=r"(o) : "r"(v), "h"(t0[e % LAG]), "h"(t1[e % LAG]));
                    v = o;
                }
                e = G - 1;
                if (e >= 0 && e < NP)
                    asm volatile("{\n\t.reg .b16 l, h;\n\tmov.b32 {l, h}, %2;\n\ttanh.approx.f16 %0, l;\n\ttanh.approx.f16 %1, h;\n\t}"
                                 : "=h"(t0[e % LAG]), "=h"(t1[e % LAG]) : "r"(zz[e & 1]));
                if (G < NP)
                    asm volatile("{\n\t.reg .b32 p;\n\tfma.rn.f16x2 p, %1, %1, %2;\n\tmul.rn.f16x2 %0, %1, p;\n\t}"
                                 : "=r"(zz[G & 1]) : "r"(h[ca & 1][gp]), "r"(0x40D940D9u));
                SCHED_FENCE();
            }
            if (!more) break;
            wg_wait<1>();
            fence_regs(st);
            norm_a();
            if (elect_one()) mbar_arrive(tbar);
            wg_fence();
            gemm1(0, 0, 6);
            wg_commit();
            SCHED_FENCE();
            wg_wait<1>();
            fence_regs(acc2);
#pragma unroll
            for (int i = 0; i < 24; ++i) y[i] = h2_to_bf2(acc2[i]);
            if (oscale != 0x3F803F80u) {
#pragma unroll
                for (int i = 0; i < 24; ++i) y[i] = hmul2_bf16(y[i], oscale);
            }
            wg_wait<0>();
        }
        wg_wait<0>();
        fence_regs(acc2);
#pragma unroll
        for (int i = 0; i < 24; ++i) y[i] = hmul2_bf16(h2_to_bf2(acc2[i]), oscale);
#pragma unroll
        for (int i = 0; i < 6; ++i) red_y(i, policy_evict_normal());
    }
}

typedef CUresult (*PFN_encodeTiled)(CUtensorMap*, CUtensorMapDataType, cuuint32_t, void*, const cuuint64_t*,
                                    const cuuint64_t*, const cuuint32_t*, const cuuint32_t*, CUtensorMapInterleave,
                                    CUtensorMapSwizzle, CUtensorMapL2promotion, CUtensorMapFloatOOBfill);

}

extern "C" void kernel_launch(void* const* d_in, const int* in_sizes, int n_in, void* d_out, int out_size) {
    const __nv_bfloat16* x = (const __nv_bfloat16*)d_in[0];
    const __nv_bfloat16* dw = (const __nv_bfloat16*)d_in[1];
    const __nv_bfloat16* w1 = (const __nv_bfloat16*)d_in[2];
    const __nv_bfloat16* b1 = (const __nv_bfloat16*)d_in[3];
    const __nv_bfloat16* w2 = (const __nv_bfloat16*)d_in[4];
    const __nv_bfloat16* b2 = (const __nv_bfloat16*)d_in[5];
    const __nv_bfloat16* gamma = (const __nv_bfloat16*)d_in[6];
    __nv_bfloat16* out = (__nv_bfloat16*)d_out;

    static PFN_encodeTiled encode = nullptr;
    if (!encode) {
        void* fn = nullptr;
        cudaDriverEntryPointQueryResult qres;
        cudaGetDriverEntryPoint("cuTensorMapEncodeTiled", &fn, cudaEnableDefault, &qres);
        encode = (PFN_encodeTiled)fn;
        cudaFuncSetAttribute(convnext_fused_kernel, cudaFuncAttributeMaxDynamicSharedMemorySize, SMEM_BYTES);
    }
    CUtensorMap xmap, w1map;
    cuuint64_t gdim[3] = {CH, IMG_W, IMG_H};
    cuuint64_t gstr[2] = {CH * 2, (cuuint64_t)IMG_W * CH * 2};
    cuuint32_t box[3] = {CH, HALF_W, 1};
    cuuint32_t estr[3] = {1, 1, 1};
    encode(&xmap, CU_TENSOR_MAP_DATA_TYPE_BFLOAT16, 3, (void*)x, gdim, gstr, box, estr, CU_TENSOR_MAP_INTERLEAVE_NONE,
           CU_TENSOR_MAP_SWIZZLE_NONE, CU_TENSOR_MAP_L2_PROMOTION_L2_128B, CU_TENSOR_MAP_FLOAT_OOB_FILL_NONE);
    cuuint64_t wdim[2] = {HID, CH};
    cuuint64_t wstr[1] = {HID * 2};
    cuuint32_t wbox[2] = {NCH, CH};
    encode(&w1map, CU_TENSOR_MAP_DATA_TYPE_BFLOAT16, 2, (void*)w1, wdim, wstr, wbox, estr, CU_TENSOR_MAP_INTERLEAVE_NONE,
           CU_TENSOR_MAP_SWIZZLE_128B, CU_TENSOR_MAP_L2_PROMOTION_L2_256B, CU_TENSOR_MAP_FLOAT_OOB_FILL_NONE);

    convnext_fused_kernel<<<NUM_CTAS, NUM_THREADS, SMEM_BYTES>>>(xmap, w1map, dw, w1, b1, w2, b2, gamma, out, 0u);
}
```

```cpp
#include <cuda_runtime.h>
#include <cuda_bf16.h>
#include <cuda.h>
#include <stdint.h>

namespace {

constexpr int IMG_H = 512, IMG_W = 512, CH = 96, HID = 384;
constexpr int STRIP_W = 64;
constexpr int NUM_STRIPS = IMG_W / STRIP_W;
constexpr int ROWS_PER_CTA = 32;
constexpr int NUM_CTAS = NUM_STRIPS * (IMG_H / ROWS_PER_CTA);
constexpr int HALF_W = STRIP_W / 2 + 3;
constexpr int HALF_BYTES = HALF_W * CH * 2;
constexpr int HALF_BOX = ((HALF_BYTES + 127) / 128) * 128;
constexpr int HALF_OFF = HALF_BOX + CH * 2;
constexpr int ROW_BYTES = 2 * HALF_BOX;
constexpr int NROW = 4;
constexpr int NA = 2;
constexpr int A_PITCH = CH * 2 + 16;
constexpr int A_HALF = 32 * A_PITCH + 64;
constexpr int A_BYTES = ((A_HALF + 32 * A_PITCH + 127) / 128) * 128;
constexpr int NCH = 64;
constexpr int NCHUNK = HID / NCH;
constexpr int NMLP = 3;

#define G1PA_ 7
#define G1PB_ 10
#define G2PA_ 13
#define RELPOS_ 94
#define REDPOS_ 8
#define REDSTEP_ 6
#define NRES 6
constexpr int LAG = 3;
constexpr int G1PA = G1PA_, G1PB = G1PB_;
constexpr int G2PA = G2PA_, G2PB = 16 + LAG;
constexpr int INITPOS = 2, REDPOS = REDPOS_, REDSTEP = REDSTEP_, TESTPOS = 76, RELPOS = RELPOS_;
constexpr int STATPOS = 80 + G2PA;
static_assert(G1PA < G1PB && G1PB < G2PA && G2PA >= 8 + LAG && G2PA < 16 && RELPOS >= STATPOS, "schedule");

constexpr int OFF_W1 = 0;
constexpr int OFF_W2 = OFF_W1 + CH * HID * 2;
constexpr int OFF_ROW = OFF_W2 + CH * HID * 2;
constexpr int OFF_A = OFF_ROW + NROW * ROW_BYTES;
constexpr int OFF_SEL = OFF_A + NA * A_BYTES;
constexpr int OFF_B2I = OFF_SEL + 256;
constexpr int OFF_MAX = OFF_B2I + 768;
constexpr int OFF_DW = OFF_MAX + 128;
constexpr int OFF_BAR = OFF_DW + 9 * CH * 2;
constexpr int BAR_ROW_FULL = 0, BAR_DONE = NROW, BAR_PRIME = BAR_DONE + NMLP, BAR_FREE = BAR_PRIME + 1, BAR_A_EMPTY = BAR_FREE + 2;
constexpr int BAR_W1 = BAR_A_EMPTY + NA, BAR_W2 = BAR_W1 + NCHUNK, BAR_DW = BAR_W2 + 4;
constexpr int BAR_W1RDY = BAR_DW + 1, BAR_W2RDY = BAR_W1RDY + 1;
constexpr int NUM_BARS = BAR_W2RDY + 1;
constexpr int SMEM_BYTES = OFF_BAR + NUM_BARS * 8;
static_assert(SMEM_BYTES <= 232448, "smem");
static_assert(HALF_OFF % 128 == 64 && OFF_ROW % 128 == 0 && OFF_SEL % 128 == 0 && OFF_B2I % 128 == 0, "bank layout");

constexpr int NUM_THREADS = 128 * (NMLP + 1);

constexpr float GELU_A = 0.7978845608028654f / 2.423828125f;
constexpr float GELU_INV2A = 0.5f / GELU_A;

__device__ __forceinline__ uint32_t smem_u32(const void* p) { return (uint32_t)__cvta_generic_to_shared(p); }

__device__ __forceinline__ void mbar_init(uint32_t bar, uint32_t count) {
    asm volatile("mbarrier.init.shared::cta.b64 [%0], %1;" ::"r"(bar), "r"(count) : "memory");
}
__device__ __forceinline__ void mbar_expect_tx(uint32_t bar, uint32_t bytes) {
    asm volatile("mbarrier.arrive.expect_tx.shared::cta.b64 _, [%0], %1;" ::"r"(bar), "r"(bytes) : "memory");
}
__device__ __forceinline__ void mbar_arrive(uint32_t bar) {
    asm volatile("mbarrier.arrive.shared::cta.b64 _, [%0];" ::"r"(bar) : "memory");
}
__device__ __forceinline__ bool mbar_test(uint32_t bar, uint32_t parity) {
    uint32_t done;
    asm volatile(
        "{\n\t.reg .pred p;\n\t"
        "mbarrier.test_wait.parity.shared::cta.b64 p, [%1], %2;\n\t"
        "selp.u32 %0, 1, 0, p;\n\t}"
        : "=r"(done) : "r"(bar), "r"(parity) : "memory");
    return done != 0;
}
__device__ __forceinline__ void mbar_wait(uint32_t bar, uint32_t parity) {
    for (int it = 0; it < (1 << 20); ++it) {
        uint32_t done;
        asm volatile(
            "{\n\t.reg .pred p;\n\t"
            "mbarrier.try_wait.parity.shared::cta.b64 p, [%1], %2;\n\t"
            "selp.u32 %0, 1, 0, p;\n\t}"
            : "=r"(done) : "r"(bar), "r"(parity) : "memory");
        if (done) break;
    }
}
__device__ __forceinline__ uint64_t policy_evict_first() {
    uint64_t p;
    asm("createpolicy.fractional.L2::evict_first.b64 %0, 1.0;" : "=l"(p));
    return p;
}
__device__ __forceinline__ uint64_t policy_evict_normal() {
    uint64_t p;
    asm("createpolicy.fractional.L2::evict_normal.b64 %0, 1.0;" : "=l"(p));
    return p;
}
__device__ __forceinline__ void tma_load_3d(uint32_t dst, const CUtensorMap* map, uint32_t bar, int c0, int c1, int c2) {
    asm volatile(
        "cp.async.bulk.tensor.3d.shared::cluster.global.mbarrier::complete_tx::bytes.L2::cache_hint [%0], [%1, {%3, %4, %5}], [%2], %6;"
        ::"r"(dst), "l"(reinterpret_cast<uint64_t>(map)), "r"(bar), "r"(c0), "r"(c1), "r"(c2), "l"(policy_evict_first()) : "memory");
}
__device__ __forceinline__ void tma_load_2d(uint32_t dst, const CUtensorMap* map, uint32_t bar, int c0, int c1) {
    asm volatile(
        "cp.async.bulk.tensor.2d.shared::cluster.global.mbarrier::complete_tx::bytes [%0], [%1, {%3, %4}], [%2];"
        ::"r"(dst), "l"(reinterpret_cast<uint64_t>(map)), "r"(bar), "r"(c0), "r"(c1) : "memory");
}
__device__ __forceinline__ bool elect_one() {
    uint32_t p;
    asm volatile("{\n\t.reg .pred p;\n\telect.sync _|p, 0xffffffff;\n\tselp.u32 %0, 1, 0, p;\n\t}" : "=r"(p));
    return p != 0;
}
__device__ __forceinline__ void bulk_load(uint32_t dst, const void* src, uint32_t bytes, uint32_t bar) {
    asm volatile("cp.async.bulk.shared::cluster.global.mbarrier::complete_tx::bytes [%0], [%1], %2, [%3];"
                 ::"r"(dst), "l"(src), "r"(bytes), "r"(bar) : "memory");
}
__device__ __forceinline__ void bulk_store(void* dst, uint32_t src, uint32_t bytes) {
    asm volatile("cp.async.bulk.global.shared::cta.bulk_group [%0], [%1], %2;" ::"l"(dst), "r"(src), "r"(bytes) : "memory");
}
__device__ __forceinline__ void bulk_commit() { asm volatile("cp.async.bulk.commit_group;" ::: "memory"); }
template <int N> __device__ __forceinline__ void bulk_wait_read() {
    asm volatile("cp.async.bulk.wait_group.read %0;" ::"n"(N) : "memory");
}
template <int N> __device__ __forceinline__ void bulk_wait() {
    asm volatile("cp.async.bulk.wait_group %0;" ::"n"(N) : "memory");
}
__device__ __forceinline__ void ldsm_x4(uint32_t addr, uint32_t& r0, uint32_t& r1, uint32_t& r2, uint32_t& r3) {
    asm volatile("ldmatrix.sync.aligned.m8n8.x4.shared.b16 {%0,%1,%2,%3}, [%4];"
                 : "=r"(r0), "=r"(r1), "=r"(r2), "=r"(r3) : "r"(addr) : "memory");
}
__device__ __forceinline__ void ldsm_x2(uint32_t addr, uint32_t& r0, uint32_t& r1) {
    asm volatile("ldmatrix.sync.aligned.m8n8.x2.shared.b16 {%0,%1}, [%2];" : "=r"(r0), "=r"(r1) : "r"(addr) : "memory");
}
__device__ __forceinline__ void stsm_x4(uint32_t addr, uint32_t r0, uint32_t r1, uint32_t r2, uint32_t r3) {
    asm volatile("stmatrix.sync.aligned.m8n8.x4.shared.b16 [%0], {%1,%2,%3,%4};"
                 ::"r"(addr), "r"(r0), "r"(r1), "r"(r2), "r"(r3) : "memory");
}
__device__ __forceinline__ uint4 lds128(uint32_t addr) {
    uint4 v;
    asm volatile("ld.shared.v4.u32 {%0,%1,%2,%3}, [%4];" : "=r"(v.x), "=r"(v.y), "=r"(v.z), "=r"(v.w) : "r"(addr) : "memory");
    return v;
}
__device__ __forceinline__ uint32_t lds32(uint32_t addr) {
    uint32_t a;
    asm volatile("ld.shared.u32 %0, [%1];" : "=r"(a) : "r"(addr) : "memory");
    return a;
}
__device__ __forceinline__ void sts32(uint32_t addr, uint32_t a) {
    asm volatile("st.shared.u32 [%0], %1;" ::"r"(addr), "r"(a) : "memory");
}
__device__ __forceinline__ void sts128(uint32_t addr, uint32_t a, uint32_t b, uint32_t c, uint32_t d) {
    asm volatile("st.shared.v4.u32 [%0], {%1,%2,%3,%4};" ::"r"(addr), "r"(a), "r"(b), "r"(c), "r"(d) : "memory");
}
__device__ __forceinline__ uint32_t hfma2_bf16(uint32_t a, uint32_t b, uint32_t c) {
    uint32_t d;
    asm("fma.rn.bf16x2 %0, %1, %2, %3;" : "=r"(d) : "r"(a), "r"(b), "r"(c));
    return d;
}
template <bool HI> __device__ __forceinline__ uint32_t hfma2_bf16_bcast(uint32_t a, uint32_t b, uint32_t c) {
    uint32_t d;
    if (HI)
        asm("{\n\t.reg .b16 a, b, c, d;\n\t.reg .b32 r, o;\n\tmov.b32 {a, b}, %2;\n\tmov.b32 {c, d}, %3;\n\t"
            "mov.b32 r, {b, b};\n\tmov.b32 o, {d, d};\n\tfma.rn.bf16x2 %0, %1, r, o;\n\t}" : "=r"(d) : "r"(a), "r"(b), "r"(c));
    else
        asm("{\n\t.reg .b16 a, b, c, d;\n\t.reg .b32 r, o;\n\tmov.b32 {a, b}, %2;\n\tmov.b32 {c, d}, %3;\n\t"
            "mov.b32 r, {a, a};\n\tmov.b32 o, {c, c};\n\tfma.rn.bf16x2 %0, %1, r, o;\n\t}" : "=r"(d) : "r"(a), "r"(b), "r"(c));
    return d;
}
__device__ __forceinline__ uint32_t hmul2_bf16(uint32_t a, uint32_t b) {
    uint32_t d;
    asm("mul.rn.bf16x2 %0, %1, %2;" : "=r"(d) : "r"(a), "r"(b));
    return d;
}
__device__ __forceinline__ uint32_t hadd2_bf16(uint32_t a, uint32_t b) {
    uint32_t d;
    asm("add.rn.bf16x2 %0, %1, %2;" : "=r"(d) : "r"(a), "r"(b));
    return d;
}
__device__ __forceinline__ float bf_lo(uint32_t v) { return __uint_as_float(v << 16); }
__device__ __forceinline__ float bf_hi(uint32_t v) { return __uint_as_float(v & 0xffff0000u); }
__device__ __forceinline__ uint32_t pack_bf16(float lo, float hi) {
    uint32_t d;
    asm("cvt.rn.bf16x2.f32 %0, %1, %2;" : "=r"(d) : "f"(hi), "f"(lo));
    return d;
}
__device__ __forceinline__ uint32_t pack_f16(float lo, float hi) {
    uint32_t d;
    asm("cvt.rn.f16x2.f32 %0, %1, %2;" : "=r"(d) : "f"(hi), "f"(lo));
    return d;
}
__device__ __forceinline__ uint32_t scale2h(uint32_t v, float s) {
    return pack_f16(bf_lo(v) * s, bf_hi(v) * s);
}
__device__ __forceinline__ uint32_t h2_to_bf2(uint32_t v) {
    uint32_t d;
    asm("{\n\t.reg .b16 l, h;\n\t.reg .f32 a, b;\n\tmov.b32 {l, h}, %1;\n\tcvt.f32.f16 a, l;\n\tcvt.f32.f16 b, h;\n\t"
        "cvt.rn.bf16x2.f32 %0, b, a;\n\t}" : "=r"(d) : "r"(v));
    return d;
}
__device__ __forceinline__ uint32_t bf2_to_h2(uint32_t y) { return (y & 0x7fff7fffu) * 7u + y; }
__device__ __forceinline__ uint32_t absmax2(uint32_t m, uint32_t v) { return __vmaxu2(m, v & 0x7fff7fffu); }
__device__ __forceinline__ void red_add_bf16x8(void* p, uint32_t a, uint32_t b, uint32_t c, uint32_t d, uint64_t pol) {
    asm volatile("red.global.add.noftz.L2::cache_hint.v4.bf16x2 [%0], {%1,%2,%3,%4}, %5;"
                 ::"l"(p), "r"(a), "r"(b), "r"(c), "r"(d), "l"(pol) : "memory");
}
__device__ __forceinline__ void wg_fence() { asm volatile("wgmma.fence.sync.aligned;" ::: "memory"); }
__device__ __forceinline__ void wg_commit() { asm volatile("wgmma.commit_group.sync.aligned;" ::: "memory"); }
template <int N> __device__ __forceinline__ void wg_wait() {
    asm volatile("wgmma.wait_group.sync.aligned %0;" ::"n"(N) : "memory");
}
template <int N> __device__ __forceinline__ void fence_regs(float (&d)[N]) {
#pragma unroll
    for (int i = 0; i < N; ++i) asm volatile("" : "+f"(d[i])::"memory");
}
template <int N> __device__ __forceinline__ void fence_regs(uint32_t (&d)[N]) {
#pragma unroll
    for (int i = 0; i < N; ++i) asm volatile("" : "+r"(d[i])::"memory");
}

template <int N> struct WH;
template <> struct WH<64> {
    static __device__ __forceinline__ void acc(uint32_t* d, uint32_t a0, uint32_t a1, uint32_t a2, uint32_t a3, uint64_t desc) {
        asm volatile("wgmma.mma_async.sync.aligned.m64n64k16.f16.f16.f16 {%0,%1,%2,%3,%4,%5,%6,%7,%8,%9,%10,%11,%12,%13,%14,%15}, "
                     "{%16,%17,%18,%19}, %20, 1, 1, 1, 1;"
                     : "+r"(d[0]), "+r"(d[1]), "+r"(d[2]), "+r"(d[3]), "+r"(d[4]), "+r"(d[5]), "+r"(d[6]), "+r"(d[7]), "+r"(d[8]), "+r"(d[9]), "+r"(d[10]), "+r"(d[11]), "+r"(d[12]), "+r"(d[13]), "+r"(d[14]), "+r"(d[15])
                     : "r"(a0), "r"(a1), "r"(a2), "r"(a3), "l"(desc) : "memory");
    }
    static __device__ __forceinline__ void first(uint32_t* d, uint32_t a0, uint32_t a1, uint32_t a2, uint32_t a3, uint64_t desc) {
        asm volatile("wgmma.mma_async.sync.aligned.m64n64k16.f16.f16.f16 {%0,%1,%2,%3,%4,%5,%6,%7,%8,%9,%10,%11,%12,%13,%14,%15}, "
                     "{%16,%17,%18,%19}, %20, 0, 1, 1, 1;"
                     : "=r"(d[0]), "=r"(d[1]), "=r"(d[2]), "=r"(d[3]), "=r"(d[4]), "=r"(d[5]), "=r"(d[6]), "=r"(d[7]), "=r"(d[8]), "=r"(d[9]), "=r"(d[10]), "=r"(d[11]), "=r"(d[12]), "=r"(d[13]), "=r"(d[14]), "=r"(d[15])
                     : "r"(a0), "r"(a1), "r"(a2), "r"(a3), "l"(desc) : "memory");
    }
};
template <> struct WH<96> {
    static __device__ __forceinline__ void acc(uint32_t* d, uint32_t a0, uint32_t a1, uint32_t a2, uint32_t a3, uint64_t desc) {
        asm volatile("wgmma.mma_async.sync.aligned.m64n96k16.f16.f16.f16 {%0,%1,%2,%3,%4,%5,%6,%7,%8,%9,%10,%11,%12,%13,%14,%15,%16,%17,%18,%19,%20,%21,%22,%23}, "
                     "{%24,%25,%26,%27}, %28, 1, 1, 1, 1;"
                     : "+r"(d[0]), "+r"(d[1]), "+r"(d[2]), "+r"(d[3]), "+r"(d[4]), "+r"(d[5]), "+r"(d[6]), "+r"(d[7]), "+r"(d[8]), "+r"(d[9]), "+r"(d[10]), "+r"(d[11]), "+r"(d[12]), "+r"(d[13]), "+r"(d[14]), "+r"(d[15]), "+r"(d[16]), "+r"(d[17]), "+r"(d[18]), "+r"(d[19]), "+r"(d[20]), "+r"(d[21]), "+r"(d[22]), "+r"(d[23])
                     : "r"(a0), "r"(a1), "r"(a2), "r"(a3), "l"(desc) : "memory");
    }
    static __device__ __forceinline__ void first(uint32_t* d, uint32_t a0, uint32_t a1, uint32_t a2, uint32_t a3, uint64_t desc) {
        asm volatile("wgmma.mma_async.sync.aligned.m64n96k16.f16.f16.f16 {%0,%1,%2,%3,%4,%5,%6,%7,%8,%9,%10,%11,%12,%13,%14,%15,%16,%17,%18,%19,%20,%21,%22,%23}, "
                     "{%24,%25,%26,%27}, %28, 0, 1, 1, 1;"
                     : "=r"(d[0]), "=r"(d[1]), "=r"(d[2]), "=r"(d[3]), "=r"(d[4]), "=r"(d[5]), "=r"(d[6]), "=r"(d[7]), "=r"(d[8]), "=r"(d[9]), "=r"(d[10]), "=r"(d[11]), "=r"(d[12]), "=r"(d[13]), "=r"(d[14]), "=r"(d[15]), "=r"(d[16]), "=r"(d[17]), "=r"(d[18]), "=r"(d[19]), "=r"(d[20]), "=r"(d[21]), "=r"(d[22]), "=r"(d[23])
                     : "r"(a0), "r"(a1), "r"(a2), "r"(a3), "l"(desc) : "memory");
    }
};

__device__ __forceinline__ void wgmma_stat(float (&d)[4], const uint32_t (&a)[4], uint64_t desc) {
    asm volatile("wgmma.mma_async.sync.aligned.m64n8k16.f32.bf16.bf16 {%0,%1,%2,%3}, {%4,%5,%6,%7}, %8, 0, 1, 1, 1;"
                 : "=f"(d[0]), "=f"(d[1]), "=f"(d[2]), "=f"(d[3]) : "r"(a[0]), "r"(a[1]), "r"(a[2]), "r"(a[3]), "l"(desc) : "memory");
}

__device__ __forceinline__ uint64_t make_desc(uint32_t addr, uint32_t lbo, uint32_t sbo) {
    return (uint64_t)((addr & 0x3FFFF) >> 4) | ((uint64_t)(lbo >> 4) << 16) | ((uint64_t)(sbo >> 4) << 32);
}

#define SCHED_FENCE() asm volatile("{\n\t.reg .pred p;\n\tsetp.ne.u32 p, %0, 0;\n\t@p exit;\n\t}" ::"r"(zero) : "memory")

__global__ void __launch_bounds__(NUM_THREADS, 1)
convnext_fused_kernel(const __grid_constant__ CUtensorMap xmap, const __grid_constant__ CUtensorMap w1map,
                      const __nv_bfloat16* __restrict__ dw, const __nv_bfloat16* __restrict__ w1,
                      const __nv_bfloat16* __restrict__ b1, const __nv_bfloat16* __restrict__ w2,
                      const __nv_bfloat16* __restrict__ b2, const __nv_bfloat16* __restrict__ gamma,
                      __nv_bfloat16* __restrict__ out, uint32_t zero) {
    extern __shared__ __align__(1024) uint8_t smem[];
    const uint32_t sbase = smem_u32(smem);
    const int tid = threadIdx.x;
    const int warp = __shfl_sync(0xffffffffu, tid >> 5, 0);
    const int lane = tid & 31;
    const int wg = warp >> 2, wr = warp & 3;
    const uint32_t bars = sbase + OFF_BAR;
    const int strip = blockIdx.x % NUM_STRIPS;
    const int band = blockIdx.x / NUM_STRIPS;
    const int dir = (band & 1) ? 1 : -1;
    const int ys = (band & 1) ? band * ROWS_PER_CTA - 1 : (band + 1) * ROWS_PER_CTA;

    auto load_row = [&](int j) {
        const uint32_t bar = bars + 8 * (BAR_ROW_FULL + (j & 3));
        const uint32_t dst = sbase + OFF_ROW + (j & 3) * ROW_BYTES;
        mbar_expect_tx(bar, 2 * HALF_BYTES);
        tma_load_3d(dst, &xmap, bar, 0, strip * STRIP_W - 1, ys + dir * j);
        tma_load_3d(dst + HALF_BOX, &xmap, bar, 0, strip * STRIP_W + 30, ys + dir * j);
    };
    auto load_w2 = [&](int s) {
        mbar_expect_tx(bars + 8 * (BAR_W2 + s), CH * HID / 2);
        bulk_load(sbase + OFF_W2 + s * (CH * HID / 2), w2 + s * (CH * HID / 4), CH * HID / 2, bars + 8 * (BAR_W2 + s));
    };
    if (warp == 11) {
        if (elect_one()) {
            asm volatile("prefetch.tensormap [%0];" ::"l"(reinterpret_cast<uint64_t>(&w1map)) : "memory");
#pragma unroll
            for (int s = 0; s < NUM_BARS; ++s)
                if (s < BAR_DONE || (s >= BAR_W1 && s <= BAR_DW)) mbar_init(bars + 8 * s, 1);
            asm volatile("fence.mbarrier_init.release.cluster;" ::: "memory");
        }
        __syncwarp();
        asm volatile("bar.arrive 2, %0;" ::"n"(NUM_THREADS) : "memory");
        if (elect_one()) {
#pragma unroll 1
            for (int s = 0; s < NCHUNK; ++s) {
                mbar_expect_tx(bars + 8 * (BAR_W1 + s), CH * NCH * 2);
                tma_load_2d(sbase + OFF_W1 + s * (CH * NCH * 2), &w1map, bars + 8 * (BAR_W1 + s), s * NCH, 0);
            }
            mbar_expect_tx(bars + 8 * BAR_DW, 9 * CH * 2);
            bulk_load(sbase + OFF_DW, dw, 9 * CH * 2, bars + 8 * BAR_DW);
            load_row(0);
            load_row(1);
            load_row(2);
#pragma unroll 1
            for (int s = 0; s < 4; ++s) load_w2(s);
            load_row(3);
        }
        __syncwarp();
        asm volatile("bar.sync 3, 64;" ::: "memory");
    } else if (warp == 9) {
        if (elect_one()) {
#pragma unroll
            for (int s = BAR_DONE; s < BAR_W1; ++s) mbar_init(bars + 8 * s, s < BAR_PRIME ? 8 : 4);
            mbar_init(bars + 8 * BAR_W1RDY, 4 * NMLP);
            mbar_init(bars + 8 * BAR_W2RDY, 8);
            asm volatile("mbarrier.arrive.shared::cta.b64 _, [%0], 4;" ::"r"(bars + 8 * BAR_DONE) : "memory");
        }
        __syncwarp();
        asm volatile("bar.arrive 3, 64;" ::: "memory");
    } else if (warp == 10) {
        if (elect_one()) asm volatile("prefetch.tensormap [%0];" ::"l"(reinterpret_cast<uint64_t>(&xmap)) : "memory");
    }

    if (wg == NMLP) {
        asm volatile("setmaxnreg.dec.sync.aligned.u32 128;");
        asm volatile("bar.sync 2, %0;" ::"n"(NUM_THREADS) : "memory");
        uint32_t w[3][3][3];
        {
            mbar_wait(bars + 8 * BAR_DW, 0);
            const uint32_t wp = sbase + OFF_DW + 48 * ((wr + (lane >> 2)) & 3) + 4 * (lane & 3) + 3 * (CH * 2);
#pragma unroll
            for (int s = 0; s < 3; ++s)
#pragma unroll
                for (int t = 0; t < 9; ++t) w[t / 3][t % 3][s] = lds32(wp + (t / 3 - 1) * dir * 3 * (CH * 2) + (t % 3) * (CH * 2) + s * 16);
        }
        const int ga = lane & 7, ja = lane >> 3;
        const uint32_t ip = sbase + OFF_ROW + (uint32_t)((ga >> 2) * HALF_OFF + (8 * (ga & 3) + ja) * (CH * 2) + 48 * ((wr + ga) & 3));
        const uint32_t op = sbase + OFF_A + (uint32_t)((ga >> 2) * A_HALF + (8 * (ga & 3) + ja) * A_PITCH + 48 * ((wr + ga) & 3));
        static_assert(NROW == 4 && NA == 2, "ring arithmetic");
        uint32_t P[2][3][8], f[10], c[8];
        auto load_window = [&](uint32_t a) {
            ldsm_x4(a, f[0], f[1], f[2], f[3]);
            ldsm_x4(a + 4 * (CH * 2), f[4], f[5], f[6], f[7]);
            ldsm_x2(a + 8 * (CH * 2), f[8], f[9]);
        };
        auto feed = [&](int e, int s, int i) {
#pragma unroll
            for (int o = i - 2; o <= i; ++o) {
                if (o < 0 || o > 7) continue;
                const int jx = i - o;
                if (jx == 0) {
                    asm volatile("fma.rn.bf16x2 %0, %3, %4, %1;\n\tfma.rn.bf16x2 %2, %3, %5, %2;\n\tmul.rn.bf16x2 %1, %3, %6;"
                                 : "=&r"(c[o]), "+r"(P[e][s][o]), "+r"(P[e ^ 1][s][o])
                                 : "r"(f[i]), "r"(w[2][0][s]), "r"(w[1][0][s]), "r"(w[0][0][s]));
                } else {
                    asm volatile("fma.rn.bf16x2 %0, %3, %4, %0;\n\tfma.rn.bf16x2 %2, %3, %5, %2;\n\tfma.rn.bf16x2 %1, %3, %6, %1;"
                                 : "+r"(c[o]), "+r"(P[e][s][o]), "+r"(P[e ^ 1][s][o])
                                 : "r"(f[i]), "r"(w[2][jx][s]), "r"(w[1][jx][s]), "r"(w[0][jx][s]));
                }
            }
        };
        __nv_bfloat16* xo = out + ((ys + dir) * IMG_W + strip * STRIP_W + wr * 16) * CH;
        const uint32_t xs = sbase + OFF_ROW + (wr >> 1) * HALF_OFF + ((wr & 1) * 16 + 1) * (CH * 2);
        mbar_wait(bars + 8 * BAR_ROW_FULL, 0);
#pragma unroll
        for (int r = 0; r < 2; ++r) {
            if (r == 1) {
                mbar_wait(bars + 8 * (BAR_ROW_FULL + 1), 0);
                if (elect_one()) bulk_store(xo, xs + ROW_BYTES, 16 * CH * 2);
                bulk_commit();
            }
#pragma unroll
            for (int s = 0; s < 3; ++s) {
                load_window(ip + r * ROW_BYTES + s * 16);
#pragma unroll
                for (int o = 0; o < 8; ++o) {
                    if (r == 1) P[0][s][o] = hfma2_bf16(f[o + 2], w[1][2][s], hfma2_bf16(f[o + 1], w[1][1][s], hfma2_bf16(f[o], w[1][0][s], P[0][s][o])));
                    P[r][s][o] = hfma2_bf16(f[o + 2], w[0][2][s], hfma2_bf16(f[o + 1], w[0][1][s], hmul2_bf16(f[o], w[0][0][s])));
                }
            }
        }
        __syncwarp();
        if (elect_one()) mbar_arrive(bars + 8 * BAR_PRIME);
        mbar_wait(bars + 8 * (BAR_ROW_FULL + 2), 0);
        load_window(ip + 2 * ROW_BYTES);
        const bool el = elect_one();
        uint32_t dbar = bars + 8 * BAR_DONE;
#pragma unroll 1
        for (int m = 0; m < ROWS_PER_CTA / 4; ++m) {
            const bool last = m + 1 == ROWS_PER_CTA / 4;
#pragma unroll
            for (int u = 0; u < 4; ++u) {
                const int j = 4 * m + u + 2;
                const int rs = (u + 2) & 3, ns = (u + 3) & 3;
                const uint32_t ebar = bars + 8 * (BAR_A_EMPTY + (u & 1)), rbar = bars + 8 * (BAR_ROW_FULL + ns);
                const uint32_t eph = ((u >> 1) & 1) ^ 1, rph = (m + (u >= 1)) & 1;
                xo += dir * IMG_W * CH;
                if (!(u == 3 && last)) {
                    if (elect_one()) bulk_store(xo, xs + rs * ROW_BYTES, 16 * CH * 2);
                }
                bulk_commit();
                bool ok = mbar_test(ebar, eph);
#pragma unroll
                for (int s = 0; s < 3; ++s) {
                    if (s == 2) ok = mbar_test(rbar, rph) || (u == 3 && last);
                    feed(u & 1, s, 0); feed(u & 1, s, 1); feed(u & 1, s, 2); feed(u & 1, s, 3);
                    if (s == 0) {
                        if (!ok) mbar_wait(ebar, eph);
                    }
                    const uint32_t nx = ip + (s == 2 ? ns : rs) * ROW_BYTES + ((s + 1) % 3) * 16;
                    const uint32_t ox = op + (u & 1) * A_BYTES + s * 16;
                    if (s < 2 || ok) ldsm_x4(nx, f[0], f[1], f[2], f[3]);
                    SCHED_FENCE();
                    feed(u & 1, s, 4); feed(u & 1, s, 5);
                    stsm_x4(ox, c[0], c[1], c[2], c[3]);
                    feed(u & 1, s, 6); feed(u & 1, s, 7);
                    ldsm_x4(nx + 4 * (CH * 2), f[4], f[5], f[6], f[7]);
                    SCHED_FENCE();
                    feed(u & 1, s, 8); feed(u & 1, s, 9);
                    stsm_x4(ox + 4 * A_PITCH, c[4], c[5], c[6], c[7]);
                    ldsm_x2(nx + 8 * (CH * 2), f[8], f[9]);
                    SCHED_FENCE();
                }
                bulk_wait<1>();
                __syncwarp();
                if (el) mbar_arrive(dbar);
                bulk_wait_read<0>();
                if (el) mbar_arrive(bars + 8 * (BAR_FREE + (u & 1)));
                dbar = dbar == bars + 8 * (BAR_DONE + NMLP - 1) ? bars + 8 * BAR_DONE : dbar + 8;
                if ((wr == u && !last) || (u == 0 && m == 0 && wr == 1)) {
                    mbar_wait(bars + 8 * (BAR_FREE + (u & 1)), (u >> 1) & 1);
                    if (elect_one()) load_row(u == 0 ? j + 4 - wr : j + 4);
                }
                if (!ok) {
                    mbar_wait(rbar, rph);
                    load_window(ip + ns * ROW_BYTES);
                }
            }
        }
    } else {
        const int g = lane >> 2, q = lane & 3;
        const uint4 r95 = __ldg(reinterpret_cast<const uint4*>(w1 + 95 * HID + (warp >> 1) * NCH + (lane & 7) * 8));
        const uint4 bb = __ldg(reinterpret_cast<const uint4*>(b1 + (warp >> 1) * NCH + (lane & 7) * 8));
        uint4 gm[3];
#pragma unroll
        for (int jj = 0; jj < 3; ++jj) gm[jj] = __ldg(reinterpret_cast<const uint4*>(gamma + jj * 32 + q * 8));
        uint32_t b2v = 0, g2v = 0;
        if (tid >= 128 && tid < 128 + CH / 2) {
            b2v = __ldg(reinterpret_cast<const uint32_t*>(b2) + tid - 128);
            g2v = __ldg(reinterpret_cast<const uint32_t*>(gamma) + tid - 128);
        }
        auto transform_w2 = [&](int s, int pass) {
            const uint32_t w2b = sbase + OFF_W2 + (warp - 4) * 6 * (8 * CH * 2);
            const float up = __uint_as_float((uint32_t)(127 + s) << 23), sc = up * GELU_INV2A;
            uint32_t gh[12];
#pragma unroll
            for (int e = 0; e < 12; ++e) {
                const uint32_t gv = (e & 3) == 0 ? gm[e / 4].x : (e & 3) == 1 ? gm[e / 4].y : (e & 3) == 2 ? gm[e / 4].z : gm[e / 4].w;
                gh[e] = pack_bf16(bf_lo(gv) * sc * 0x1p-112f, bf_hi(gv) * sc * 0x1p-112f);
            }
            if (tid < 128 + CH / 2) {
                const uint32_t v2 = pack_f16(bf_lo(b2v) * bf_lo(g2v) * up, bf_hi(b2v) * bf_hi(g2v) * up);
                const uint32_t a = sbase + OFF_B2I + (((tid >> 4) & 3) * 2 + ((tid >> 1) & 1)) * 128 + ((tid >> 2) & 3) * 16 + (tid & 1) * 8;
                sts32(a, v2); sts32(a + 4, v2);
                sts32(a + 64, 0); sts32(a + 68, 0);
            }
            mbar_wait(bars + 8 * (BAR_W2 + (warp >> 1) - 2), pass);
            uint4 v[3];
#pragma unroll
            for (int jj = 0; jj < 3; ++jj) v[jj] = lds128(w2b + g * (CH * 2) + jj * 64 + q * 16);
            uint32_t mu = 0, ms = 0;
#pragma unroll 1
            for (int i = 0; i < 6; ++i) {
                uint32_t o[12];
#pragma unroll
                for (int jj = 0; jj < 3; ++jj) {
                    mu = __vmaxu2(__vmaxu2(mu, v[jj].x), v[jj].y); mu = __vmaxu2(__vmaxu2(mu, v[jj].z), v[jj].w);
                    ms = __vmaxs2(__vmaxs2(ms, v[jj].x), v[jj].y); ms = __vmaxs2(__vmaxs2(ms, v[jj].z), v[jj].w);
                    o[jj * 4 + 0] = hmul2_bf16(v[jj].x, gh[jj * 4 + 0]);
                    o[jj * 4 + 1] = hmul2_bf16(v[jj].y, gh[jj * 4 + 1]);
                    o[jj * 4 + 2] = hmul2_bf16(v[jj].z, gh[jj * 4 + 2]);
                    o[jj * 4 + 3] = hmul2_bf16(v[jj].w, gh[jj * 4 + 3]);
                    if (i < 5) v[jj] = lds128(w2b + (i + 1) * (8 * CH * 2) + g * (CH * 2) + jj * 64 + q * 16);
                }
                __syncwarp();
#pragma unroll
                for (int e = 0; e < 12; ++e) o[e] = bf2_to_h2(o[e]);
#pragma unroll
                for (int jj = 0; jj < 3; ++jj)
                    stsm_x4(w2b + i * (8 * CH * 2) + jj * 512 + lane * 16, o[jj * 4], o[jj * 4 + 1], o[jj * 4 + 2], o[jj * 4 + 3]);
            }
            mu = __vmaxu2(mu & 0x7fff7fffu, ms);
            return __reduce_max_sync(0xffffffffu, max(mu & 0xffffu, mu >> 16));
        };
        if (warp != 11) asm volatile("bar.sync 2, %0;" ::"n"(NUM_THREADS) : "memory");
        asm volatile("setmaxnreg.inc.sync.aligned.u32 128;");
        {
            const int box = warp >> 1, cc = lane & 7, k0 = (warp & 1) * 48 + (lane >> 3);
            constexpr uint32_t DN = 0x07800780u;
            if (tid < 16) {
                const uint32_t v = tid < 8 ? 0x3F80u : 0x3F800000u;
                sts128(sbase + OFF_SEL + tid * 16, v, v, v, v);
            }
            const uint32_t m[4] = {hmul2_bf16(r95.x, DN | 0x80008000u), hmul2_bf16(r95.y, DN | 0x80008000u),
                                   hmul2_bf16(r95.z, DN | 0x80008000u), hmul2_bf16(r95.w, DN | 0x80008000u)};
            const uint32_t tb[4] = {scale2h(bb.x, GELU_A), scale2h(bb.y, GELU_A), scale2h(bb.z, GELU_A), scale2h(bb.w, GELU_A)};
            uint32_t mx = absmax2(absmax2(absmax2(absmax2(0, hmul2_bf16(bb.x, DN)), hmul2_bf16(bb.y, DN)), hmul2_bf16(bb.z, DN)), hmul2_bf16(bb.w, DN));
            uint32_t mg = 0;
#pragma unroll
            for (int jj = 0; jj < 3; ++jj) mg = absmax2(absmax2(absmax2(absmax2(mg, gm[jj].x), gm[jj].y), gm[jj].z), gm[jj].w);
            mg = __reduce_max_sync(0xffffffffu, max(mg & 0xffffu, mg >> 16));
            if (warp == 4 || warp == 5) {
                const uint32_t mb = __reduce_max_sync(0xffffffffu, max(b2v & 0x7fffu, (b2v >> 16) & 0x7fffu));
                if (lane == 0) sts32(sbase + OFF_MAX + 32 + warp * 4, mb);
            }
            const uint32_t wb = sbase + OFF_W1 + box * (CH * NCH * 2);
            const uint32_t wa[2] = {wb + k0 * 128 + ((cc ^ (k0 & 7)) << 4), wb + (k0 + 4) * 128 + ((cc ^ ((k0 + 4) & 7)) << 4)};
            mbar_wait(bars + 8 * (BAR_W1 + box), 0);
            uint4 u[2] = {lds128(wa[0]), lds128(wa[1])};
#pragma unroll 1
            for (int i = 0; i < 6; ++i) {
                uint32_t t[2][4];
#pragma unroll
                for (int e = 0; e < 2; ++e) {
                    t[e][0] = hfma2_bf16(u[e].x, DN, m[0]); t[e][1] = hfma2_bf16(u[e].y, DN, m[1]);
                    t[e][2] = hfma2_bf16(u[e].z, DN, m[2]); t[e][3] = hfma2_bf16(u[e].w, DN, m[3]);
                    if (i < 5) u[e] = lds128(wa[e] + (i + 1) * 1024);
#pragma unroll
                    for (int x = 0; x < 4; ++x) {
                        mx = absmax2(mx, t[e][x]);
                        t[e][x] = bf2_to_h2(t[e][x]);
                    }
                }
                sts128(wa[0] + i * 1024, t[0][0], t[0][1], t[0][2], t[0][3]);
                sts128(wa[1] + i * 1024, t[1][0], t[1][1], t[1][2], t[1][3]);
            }
            if (k0 + 44 == 95) sts128(wa[1] + 5 * 1024, tb[0], tb[1], tb[2], tb[3]);
            const uint32_t m1w = __reduce_max_sync(0xffffffffu, max(mx & 0xffffu, mx >> 16));
            if (lane == 0) sts32(sbase + OFF_MAX + warp * 4, m1w << 16);
            asm volatile("fence.proxy.async.shared::cta;" ::: "memory");
            __syncwarp();
            if (elect_one()) mbar_arrive(bars + 8 * BAR_W1RDY);
            if (wg > 0) {
                const uint32_t m2w = transform_w2(0, 0);
                if (lane == 0) sts32(sbase + OFF_MAX + warp * 4, m2w | (m1w << 16));
                asm volatile("fence.proxy.async.shared::cta;" ::: "memory");
                mbar_wait(bars + 8 * BAR_W1RDY, 0);
                asm volatile("bar.sync 1, 256;" ::: "memory");
                const uint32_t mm = lane < 14 ? lds32(sbase + OFF_MAX + lane * 4) : 0;
                const uint32_t m1 = __reduce_max_sync(0xffffffffu, lane < 12 ? mm >> 16 : 0);
                const uint32_t m2 = __reduce_max_sync(0xffffffffu, lane < 12 ? mm & 0xffffu : 0), mb = __reduce_max_sync(0xffffffffu, lane < 12 ? 0 : mm);
                const int e1 = max((int)(m1 >> 7), 1) - 14, eg = (int)(mg >> 7) - 126, ew = (int)(m2 >> 7) - 126;
                const int e2 = ew + eg + 1, eb = (int)(mb >> 7) - 126 + eg;
                int s = min(min(-1 - e1 - e2, 14 - eb), 14 - e2);
                if (s >= 0 && s <= 12 && e2 >= -9 && eg >= -9) s = 0;
                s = min(max(s, -120), min(120, 120 - eg));
                if (s != 0) {
                    if ((warp & 1) == 0 && elect_one()) load_w2((warp >> 1) - 2);
                    transform_w2(s, 1);
                    asm volatile("fence.proxy.async.shared::cta;" ::: "memory");
                }
                if (tid == 128) sts32(sbase + OFF_MAX + 64, (uint32_t)(127 - s) * 0x00800080u);
                __syncwarp();
                if (elect_one()) mbar_arrive(bars + 8 * BAR_W2RDY);
            } else if (wr == 0) {
                mbar_wait(bars + 8 * BAR_PRIME, 0);
                if (elect_one()) load_row(4);
            }
        }
        const uint64_t descW1 = make_desc(sbase + OFF_W1, CH * NCH * 2, 1024) | (1ull << 62);
        const uint64_t descW2 = make_desc(sbase + OFF_W2, (CH / 8) * 128, 128);
        const uint64_t descW2r = (make_desc(0, 0, 128) & ~0xffffffffull) |
                                __shfl_sync(0xffffffffu, (uint32_t)make_desc(sbase + OFF_W2, (CH / 8) * 128, 128), 0);
        const uint64_t descS = make_desc(sbase + OFF_SEL, 128, 128);
        uint32_t la = sbase + OFF_A + (wg & 1) * A_BYTES + wr * 16 * A_PITCH + (wr >> 1) * 64 +
                      (uint32_t)(((lane & 7) + ((lane >> 3) & 1) * 8) * A_PITCH + (lane >> 4) * 16);

        uint32_t acc2[24];
        uint32_t h[2][NCH / 4];
        uint32_t a1[6][4];
        uint32_t pp[4];
        float st[4];

        auto load_a = [&]() {
#pragma unroll
            for (int kb = 0; kb < 6; ++kb) ldsm_x4(la + kb * 32, a1[kb][0], a1[kb][1], a1[kb][2], a1[kb][3]);
        };
        auto partial_a = [&](int i) {
            uint32_t s = hadd2_bf16(hadd2_bf16(hadd2_bf16(a1[0][i], a1[1][i]), hadd2_bf16(a1[2][i], a1[3][i])), hadd2_bf16(a1[4][i], a1[5][i]));
            uint32_t v = hmul2_bf16(a1[0][i], a1[0][i]);
#pragma unroll
            for (int kb = 1; kb < 6; ++kb) v = hfma2_bf16(a1[kb][i], a1[kb][i], v);
            if (i >= 2) { s = hadd2_bf16(s, pp[i & 1]); v = hadd2_bf16(v, pp[2 + (i & 1)]); }
            asm volatile("" : "+r"(s), "+r"(v));
            pp[i & 1] = s; pp[2 + (i & 1)] = v;
        };
        uint32_t sel95 = q == 3 ? 0x7610 : 0x3210;
        asm volatile("" : "+r"(sel95));
        auto norm_a = [&]() {
            constexpr float K = GELU_A * 0x1p-112f, SQ = 9.797958971132712f;
            float m0 = st[0] * (-1.f / CH), m1 = st[2] * (-1.f / CH);
            float r0, r1;
            asm("rsqrt.approx.ftz.f32 %0, %1;" : "=f"(r0) : "f"(fmaf(m0, st[0], st[1]) + CH * 1e-5f));
            asm("rsqrt.approx.ftz.f32 %0, %1;" : "=f"(r1) : "f"(fmaf(m1, st[2], st[3]) + CH * 1e-5f));
            const uint32_t rp = pack_bf16(r0 * (K * SQ), r1 * (K * SQ));
            const float o0 = m0 * bf_lo(rp), o1 = m1 * bf_hi(rp);
            const uint32_t op = pack_bf16(o0, o1);
            const bool easy = (fabsf(o0) < 0.5f * K) & (fabsf(o1) < 0.5f * K) & (fminf(r0, r1) > 0x1p-12f);
            if (__all_sync(0xffffffffu, easy)) {
#pragma unroll
                for (int kb = 0; kb < 6; ++kb)
#pragma unroll
                    for (int i = 0; i < 4; ++i)
                        a1[kb][i] = bf2_to_h2((i & 1) ? hfma2_bf16_bcast<true>(a1[kb][i], rp, op) : hfma2_bf16_bcast<false>(a1[kb][i], rp, op));
            } else {
                float s0[2] = {0.f, 0.f}, s1[2] = {0.f, 0.f}, v0[2] = {0.f, 0.f}, v1[2] = {0.f, 0.f};
#pragma unroll
                for (int kb = 0; kb < 6; ++kb)
#pragma unroll
                    for (int i = 0; i < 2; ++i) {
                        float a = bf_lo(a1[kb][2 * i]), b = bf_hi(a1[kb][2 * i]);
                        s0[0] += a; v0[0] = fmaf(a, a, v0[0]); s0[1] += b; v0[1] = fmaf(b, b, v0[1]);
                        a = bf_lo(a1[kb][2 * i + 1]); b = bf_hi(a1[kb][2 * i + 1]);
                        s1[0] += a; v1[0] = fmaf(a, a, v1[0]); s1[1] += b; v1[1] = fmaf(b, b, v1[1]);
                    }
                float sa = s0[0] + s0[1], sb = s1[0] + s1[1], va = v0[0] + v0[1], vb = v1[0] + v1[1];
                sa += __shfl_xor_sync(0xffffffffu, sa, 1); sb += __shfl_xor_sync(0xffffffffu, sb, 1);
                va += __shfl_xor_sync(0xffffffffu, va, 1); vb += __shfl_xor_sync(0xffffffffu, vb, 1);
                sa += __shfl_xor_sync(0xffffffffu, sa, 2); sb += __shfl_xor_sync(0xffffffffu, sb, 2);
                va += __shfl_xor_sync(0xffffffffu, va, 2); vb += __shfl_xor_sync(0xffffffffu, vb, 2);
                m0 = sa * (1.f / CH); m1 = sb * (1.f / CH);
                asm("rsqrt.approx.ftz.f32 %0, %1;" : "=f"(r0) : "f"(fmaxf(fmaf(-m0, m0, va * (1.f / CH)), 0.f) + 1e-5f));
                asm("rsqrt.approx.ftz.f32 %0, %1;" : "=f"(r1) : "f"(fmaxf(fmaf(-m1, m1, vb * (1.f / CH)), 0.f) + 1e-5f));
                r0 *= GELU_A; r1 *= GELU_A;
                const float p0 = -m0 * r0, p1 = -m1 * r1;
#pragma unroll
                for (int kb = 0; kb < 6; ++kb)
#pragma unroll
                    for (int i = 0; i < 4; ++i) {
                        const float r = (i & 1) ? r1 : r0, o = (i & 1) ? p1 : p0;
                        a1[kb][i] = pack_f16(fmaf(bf_lo(a1[kb][i]), r, o), fmaf(bf_hi(a1[kb][i]), r, o));
                    }
            }
            a1[5][2] = __byte_perm(a1[5][2], 0x3C000000u, sel95);
            a1[5][3] = __byte_perm(a1[5][3], 0x3C000000u, sel95);
        };
        auto gemm1 = [&](int c, int k0, int k1) {
#pragma unroll
            for (int kk = k0; kk < k1; ++kk) {
                if (kk == 0) WH<NCH>::first(h[c & 1], a1[0][0], a1[0][1], a1[0][2], a1[0][3], descW1 + (uint64_t)(c * 768));
                else WH<NCH>::acc(h[c & 1], a1[kk][0], a1[kk][1], a1[kk][2], a1[kk][3], descW1 + (uint64_t)(c * 768 + kk * 128));
            }
        };
        auto gemm2 = [&](int c, int k0, int k1) {
#pragma unroll
            for (int kk = k0; kk < k1; ++kk)
                WH<96>::acc(acc2, h[c & 1][kk * 4], h[c & 1][kk * 4 + 1], h[c & 1][kk * 4 + 2], h[c & 1][kk * 4 + 3],
                            (c * 4 + kk < NRES ? descW2r : descW2) + (uint64_t)(((c * (NCH / 8) + 2 * kk) * (CH / 8)) * 8));
        };
        uint32_t b2a = sbase + OFF_B2I + q * 16;
        asm volatile("" : "+r"(b2a));

        mbar_wait(bars + 8 * BAR_W1RDY, 0);
        static_assert((OFF_BAR + 8 * BAR_A_EMPTY) % 16 == 0 && (NMLP & 1), "the conv-tile slot alternates");
        const uint32_t nbar = bars + 8 * (BAR_DONE + wg), tbar = bars + 8 * (BAR_DONE + (wg + 1) % NMLP);
        uint32_t ebar = bars + 8 * (BAR_A_EMPTY + (wg & 1)), nph = 0;
        const uint32_t lsum = 2 * la + ((wg & 1) ? -A_BYTES : A_BYTES);
        mbar_wait(nbar, 0);
        load_a();
#pragma unroll
        for (int i = 0; i < 4; ++i) partial_a(i);
        wg_fence();
        wgmma_stat(st, pp, descS);
        wg_commit();
        __syncwarp();
        if (elect_one()) {
            mbar_arrive(ebar);
            mbar_arrive(tbar);
        }
        wg_wait<0>();
        fence_regs(st);
        norm_a();
        wg_fence();
        gemm1(0, 0, 6);
        wg_commit();
        mbar_wait(bars + 8 * BAR_W2RDY, 0);
        const uint32_t oscale = lds32(sbase + OFF_MAX + 64);
        uint32_t y[24];
#pragma unroll
        for (int m = 0; m < 6; ++m) {
            const uint4 v = lds128(b2a + m * 128);
            y[4 * m] = y[4 * m + 1] = hmul2_bf16(h2_to_bf2(v.x), oscale);
            y[4 * m + 2] = y[4 * m + 3] = hmul2_bf16(h2_to_bf2(v.z), oscale);
        }
        wg_wait<0>();
        b2a += 64;
        __nv_bfloat16* optr = out + ((ys + dir * (wg + 1)) * IMG_W + strip * STRIP_W + wr * 16 + g) * CH + q * 8;
        auto red_y = [&](int i, uint64_t pol) {
            const int jj = i / 2, hrow = i % 2;
            red_add_bf16x8(optr + hrow * 8 * CH + jj * 32, y[jj * 8 + hrow], y[jj * 8 + hrow + 2], y[jj * 8 + hrow + 4], y[jj * 8 + hrow + 6], pol);
        };
        uint64_t rpol = policy_evict_normal();
        long long ostep = 0;
#pragma unroll 1
        for (int t = wg;; t += NMLP) {
            const bool more = t + NMLP < ROWS_PER_CTA;
            bool ready = true;
            SCHED_FENCE();
            constexpr int P = NCH / 4, NP = HID / 4;
            uint32_t zz[2];
            uint16_t t0[LAG], t1[LAG];
#pragma unroll
            for (int G = 0; G <= NP + LAG; ++G) {
                const int ca = G / P, gp = G % P;
                if (G == TESTPOS) ready = mbar_test(nbar, nph);
                if (G == NP - P && !ready) mbar_wait(nbar, nph);
                if (gp == 0 && ca >= 1 && G < NP) { wg_wait<1>(); fence_regs(h[ca & 1]); }
                if (G == NP - P) load_a();
                if (ca + 1 < NCHUNK && gp == (ca == 0 ? 1 : G1PA)) {
                    if (ca > 0) wg_wait<0>();
                    wg_fence();
                    gemm1(ca + 1, 0, 3);
                }
                if (ca + 1 < NCHUNK && gp == (ca == 0 ? 3 : G1PB)) {
                    wg_fence();
                    gemm1(ca + 1, 3, 6);
                    wg_commit();
                }
                if (ca < NCHUNK && gp == G2PA) {
                    fence_regs(h[ca & 1]);
                    wg_fence();
                    if (G == STATPOS) wgmma_stat(st, pp, descS);
                    gemm2(ca, 0, 2);
                    wg_commit();
                }
                if (ca >= 1 && gp == G2PB - P) {
                    fence_regs(h[(ca - 1) & 1]);
                    wg_fence();
                    gemm2(ca - 1, 2, 4);
                    wg_commit();
                }
                if (G == INITPOS) {
#pragma unroll
                    for (int m = 0; m < 6; ++m) {
                        const uint4 v = lds128(b2a + m * 128);
                        acc2[4 * m] = v.x; acc2[4 * m + 1] = v.y; acc2[4 * m + 2] = v.z; acc2[4 * m + 3] = v.w;
                    }
                }
                if (G == RELPOS) {
                    __syncwarp();
                    if (lane == 0) mbar_arrive(ebar);
                }
                if (G >= REDPOS && G < REDPOS + 6 * REDSTEP && (G - REDPOS) % REDSTEP == 0) red_y((G - REDPOS) / REDSTEP, rpol);
                if (G == 4 * P + 4) {
                    asm volatile("sub.u32 %0, %1, %0;" : "+r"(la) : "r"(lsum));
                    asm volatile("and.b32 %0, %0, 0xffffffbf;" : "+r"(b2a));
                    ebar = more ? ebar ^ 8 : bars + 8 * BAR_DW;
                    nph ^= more;
                    asm volatile("add.u64 %0, %0, %1;" : "+l"(optr) : "l"(ostep));
                    ostep = (long long)dir * (NMLP * IMG_W * CH * 2);
                    rpol = policy_evict_first();
                }
                if (G >= STATPOS - 4 && G < STATPOS) partial_a(G - (STATPOS - 4));
                int e = G - LAG;
                if (e >= 0 && e < NP) {
                    uint32_t& v = h[(e / P) & 1][e % P];
                    uint32_t o;
                    asm volatile("{\n\t.reg .b32 t;\n\tmov.b32 t, {%2, %3};\n\tfma.rn.f16x2 %0, %1, t, %1;\n\t}"
                                 : "=r"(o) : "r"(v), "h"(t0[e % LAG]), "h"(t1[e % LAG]));
                    v = o;
                }
                e = G - 1;
                if (e >= 0 && e < NP)
                    asm volatile("{\n\t.reg .b16 l, h;\n\tmov.b32 {l, h}, %2;\n\ttanh.approx.f16 %0, l;\n\ttanh.approx.f16 %1, h;\n\t}"
                                 : "=h"(t0[e % LAG]), "=h"(t1[e % LAG]) : "r"(zz[e & 1]));
                if (G < NP)
                    asm volatile("{\n\t.reg .b32 p;\n\tfma.rn.f16x2 p, %1, %1, %2;\n\tmul.rn.f16x2 %0, %1, p;\n\t}"
                                 : "=r"(zz[G & 1]) : "r"(h[ca & 1][gp]), "r"(0x40D940D9u));
                SCHED_FENCE();
            }
            if (!more) break;
            wg_wait<1>();
            fence_regs(st);
            norm_a();
            if (lane == 0) mbar_arrive(tbar);
            wg_fence();
            gemm1(0, 0, 6);
            wg_commit();
            SCHED_FENCE();
            wg_wait<1>();
            fence_regs(acc2);
#pragma unroll
            for (int i = 0; i < 24; ++i) y[i] = h2_to_bf2(acc2[i]);
            if (oscale != 0x3F803F80u) {
#pragma unroll
                for (int i = 0; i < 24; ++i) y[i] = hmul2_bf16(y[i], oscale);
            }
            wg_wait<0>();
        }
        wg_wait<0>();
        fence_regs(acc2);
#pragma unroll
        for (int i = 0; i < 24; ++i) y[i] = hmul2_bf16(h2_to_bf2(acc2[i]), oscale);
#pragma unroll
        for (int i = 0; i < 6; ++i) red_y(i, policy_evict_normal());
    }
}

typedef CUresult (*PFN_encodeTiled)(CUtensorMap*, CUtensorMapDataType, cuuint32_t, void*, const cuuint64_t*,
                                    const cuuint64_t*, const cuuint32_t*, const cuuint32_t*, CUtensorMapInterleave,
                                    CUtensorMapSwizzle, CUtensorMapL2promotion, CUtensorMapFloatOOBfill);

}

extern "C" void kernel_launch(void* const* d_in, const int* in_sizes, int n_in, void* d_out, int out_size) {
    const __nv_bfloat16* x = (const __nv_bfloat16*)d_in[0];
    const __nv_bfloat16* dw = (const __nv_bfloat16*)d_in[1];
    const __nv_bfloat16* w1 = (const __nv_bfloat16*)d_in[2];
    const __nv_bfloat16* b1 = (const __nv_bfloat16*)d_in[3];
    const __nv_bfloat16* w2 = (const __nv_bfloat16*)d_in[4];
    const __nv_bfloat16* b2 = (const __nv_bfloat16*)d_in[5];
    const __nv_bfloat16* gamma = (const __nv_bfloat16*)d_in[6];
    __nv_bfloat16* out = (__nv_bfloat16*)d_out;

    static PFN_encodeTiled encode = nullptr;
    if (!encode) {
        void* fn = nullptr;
        cudaDriverEntryPointQueryResult qres;
        cudaGetDriverEntryPoint("cuTensorMapEncodeTiled", &fn, cudaEnableDefault, &qres);
        encode = (PFN_encodeTiled)fn;
        cudaFuncSetAttribute(convnext_fused_kernel, cudaFuncAttributeMaxDynamicSharedMemorySize, SMEM_BYTES);
    }
    CUtensorMap xmap, w1map;
    cuuint64_t gdim[3] = {CH, IMG_W, IMG_H};
    cuuint64_t gstr[2] = {CH * 2, (cuuint64_t)IMG_W * CH * 2};
    cuuint32_t box[3] = {CH, HALF_W, 1};
    cuuint32_t estr[3] = {1, 1, 1};
    encode(&xmap, CU_TENSOR_MAP_DATA_TYPE_BFLOAT16, 3, (void*)x, gdim, gstr, box, estr, CU_TENSOR_MAP_INTERLEAVE_NONE,
           CU_TENSOR_MAP_SWIZZLE_NONE, CU_TENSOR_MAP_L2_PROMOTION_L2_128B, CU_TENSOR_MAP_FLOAT_OOB_FILL_NONE);
    cuuint64_t wdim[2] = {HID, CH};
    cuuint64_t wstr[1] = {HID * 2};
    cuuint32_t wbox[2] = {NCH, CH};
    encode(&w1map, CU_TENSOR_MAP_DATA_TYPE_BFLOAT16, 2, (void*)w1, wdim, wstr, wbox, estr, CU_TENSOR_MAP_INTERLEAVE_NONE,
           CU_TENSOR_MAP_SWIZZLE_128B, CU_TENSOR_MAP_L2_PROMOTION_L2_256B, CU_TENSOR_MAP_FLOAT_OOB_FILL_NONE);

    convnext_fused_kernel<<<NUM_CTAS, NUM_THREADS, SMEM_BYTES>>>(xmap, w1map, dw, w1, b1, w2, b2, gamma, out, 0u);
}
```

```cpp
#include <cuda_runtime.h>
#include <cuda_bf16.h>
#include <cuda.h>
#include <stdint.h>

namespace {

constexpr int IMG_H = 512, IMG_W = 512, CH = 96, HID = 384;
constexpr int STRIP_W = 64;
constexpr int NUM_STRIPS = IMG_W / STRIP_W;
constexpr int ROWS_PER_CTA = 32;
constexpr int NUM_CTAS = NUM_STRIPS * (IMG_H / ROWS_PER_CTA);
constexpr int HALF_W = STRIP_W / 2 + 3;
constexpr int HALF_BYTES = HALF_W * CH * 2;
constexpr int HALF_BOX = ((HALF_BYTES + 127) / 128) * 128;
constexpr int HALF_OFF = HALF_BOX + CH * 2;
constexpr int ROW_BYTES = 2 * HALF_BOX;
constexpr int NROW = 4;
constexpr int NA = 2;
constexpr int A_PITCH = CH * 2 + 16;
constexpr int A_HALF = 32 * A_PITCH + 64;
constexpr int A_BYTES = ((A_HALF + 32 * A_PITCH + 127) / 128) * 128;
constexpr int NCH = 64;
constexpr int NCHUNK = HID / NCH;
constexpr int NMLP = 3;

constexpr int LAG = 3;
constexpr int G1PA = 7, G1PB = 10;
constexpr int G2PA = 13, G2PB = 16 + LAG;
constexpr int INITPOS = 2;
constexpr int REDPOS = 9, REDSTEP = 8;
constexpr int UPDPOS = 57;
constexpr int PICKPOS = 73, TESTPOS = PICKPOS - 4;
constexpr int STATPOS = 80 + G2PA;
constexpr int RELPOS = 94;
constexpr int NRES = 6;
constexpr int NFREE = 1;
static_assert(G1PA < G1PB && G1PB < G2PA && G2PA >= 8 + LAG && G2PA < 16 && RELPOS > STATPOS - 4 &&
              REDPOS + 5 * REDSTEP < UPDPOS && UPDPOS < TESTPOS, "schedule");

constexpr int OFF_W1 = 0;
constexpr int OFF_W2 = OFF_W1 + CH * HID * 2;
constexpr int OFF_ROW = OFF_W2 + CH * HID * 2;
constexpr int OFF_A = OFF_ROW + NROW * ROW_BYTES;
constexpr int OFF_SEL = OFF_A + NA * A_BYTES;
constexpr int OFF_B2I = OFF_SEL + 256;
constexpr int OFF_MAX = OFF_B2I + 768;
constexpr int OFF_DW = OFF_MAX + 128;
constexpr int OFF_BAR = OFF_DW + 9 * CH * 2;
constexpr int BAR_ROW_FULL = 0, BAR_DONE = NROW, BAR_PRIME = BAR_DONE + NMLP, BAR_FREE = BAR_PRIME + 1, BAR_A_EMPTY = BAR_FREE + 2;
constexpr int BAR_W1 = BAR_A_EMPTY + NA, BAR_W2 = BAR_W1 + NCHUNK, BAR_DW = BAR_W2 + 4;
constexpr int BAR_W1RDY = BAR_DW + 1, BAR_W2RDY = BAR_W1RDY + 1;
constexpr int NUM_BARS = BAR_W2RDY + 1;
constexpr int SMEM_BYTES = OFF_BAR + NUM_BARS * 8;
static_assert(SMEM_BYTES <= 232448, "smem");
static_assert(HALF_OFF % 128 == 64 && OFF_ROW % 128 == 0 && OFF_SEL % 128 == 0 && OFF_B2I % 128 == 0, "bank layout");

constexpr int NUM_THREADS = 128 * (NMLP + 1);

constexpr float GELU_A = 0.7978845608028654f / 2.423828125f;
constexpr float GELU_INV2A = 0.5f / GELU_A;

__device__ __forceinline__ uint32_t smem_u32(const void* p) { return (uint32_t)__cvta_generic_to_shared(p); }

__device__ __forceinline__ void mbar_init(uint32_t bar, uint32_t count) {
    asm volatile("mbarrier.init.shared::cta.b64 [%0], %1;" ::"r"(bar), "r"(count) : "memory");
}
__device__ __forceinline__ void mbar_expect_tx(uint32_t bar, uint32_t bytes) {
    asm volatile("mbarrier.arrive.expect_tx.shared::cta.b64 _, [%0], %1;" ::"r"(bar), "r"(bytes) : "memory");
}
__device__ __forceinline__ void mbar_arrive(uint32_t bar) {
    asm volatile("mbarrier.arrive.shared::cta.b64 _, [%0];" ::"r"(bar) : "memory");
}
__device__ __forceinline__ bool mbar_test(uint32_t bar, uint32_t parity) {
    uint32_t done;
    asm volatile(
        "{\n\t.reg .pred p;\n\t"
        "mbarrier.test_wait.parity.shared::cta.b64 p, [%1], %2;\n\t"
        "selp.u32 %0, 1, 0, p;\n\t}"
        : "=r"(done) : "r"(bar), "r"(parity) : "memory");
    return done != 0;
}
__device__ __forceinline__ void mbar_wait(uint32_t bar, uint32_t parity) {
    uint32_t done = 0;
    for (int it = 0; it < (1 << 20); ++it) {
        asm volatile(
            "{\n\t.reg .pred p;\n\t"
            "mbarrier.try_wait.parity.shared::cta.b64 p, [%1], %2;\n\t"
            "selp.u32 %0, 1, 0, p;\n\t}"
            : "=r"(done) : "r"(bar), "r"(parity) : "memory");
        if (done) break;
    }
}
__device__ __forceinline__ uint64_t policy_evict_first() {
    uint64_t p;
    asm("createpolicy.fractional.L2::evict_first.b64 %0, 1.0;" : "=l"(p));
    return p;
}
__device__ __forceinline__ uint64_t policy_evict_normal() {
    uint64_t p;
    asm("createpolicy.fractional.L2::evict_normal.b64 %0, 1.0;" : "=l"(p));
    return p;
}
__device__ __forceinline__ void tma_load_3d(uint32_t dst, const CUtensorMap* map, uint32_t bar, int c0, int c1, int c2) {
    asm volatile(
        "cp.async.bulk.tensor.3d.shared::cluster.global.mbarrier::complete_tx::bytes.L2::cache_hint [%0], [%1, {%3, %4, %5}], [%2], %6;"
        ::"r"(dst), "l"(reinterpret_cast<uint64_t>(map)), "r"(bar), "r"(c0), "r"(c1), "r"(c2), "l"(policy_evict_first()) : "memory");
}
__device__ __forceinline__ void tma_load_2d(uint32_t dst, const CUtensorMap* map, uint32_t bar, int c0, int c1) {
    asm volatile(
        "cp.async.bulk.tensor.2d.shared::cluster.global.mbarrier::complete_tx::bytes [%0], [%1, {%3, %4}], [%2];"
        ::"r"(dst), "l"(reinterpret_cast<uint64_t>(map)), "r"(bar), "r"(c0), "r"(c1) : "memory");
}
__device__ __forceinline__ bool elect_one() {
    uint32_t p;
    asm volatile("{\n\t.reg .pred p;\n\telect.sync _|p, 0xffffffff;\n\tselp.u32 %0, 1, 0, p;\n\t}" : "=r"(p));
    return p != 0;
}
__device__ __forceinline__ void bulk_load(uint32_t dst, const void* src, uint32_t bytes, uint32_t bar) {
    asm volatile("cp.async.bulk.shared::cluster.global.mbarrier::complete_tx::bytes [%0], [%1], %2, [%3];"
                 ::"r"(dst), "l"(src), "r"(bytes), "r"(bar) : "memory");
}
__device__ __forceinline__ void bulk_store(void* dst, uint32_t src, uint32_t bytes) {
    asm volatile("cp.async.bulk.global.shared::cta.bulk_group [%0], [%1], %2;" ::"l"(dst), "r"(src), "r"(bytes) : "memory");
}
__device__ __forceinline__ void bulk_commit() { asm volatile("cp.async.bulk.commit_group;" ::: "memory"); }
template <int N> __device__ __forceinline__ void bulk_wait_read() {
    asm volatile("cp.async.bulk.wait_group.read %0;" ::"n"(N) : "memory");
}
template <int N> __device__ __forceinline__ void bulk_wait() {
    asm volatile("cp.async.bulk.wait_group %0;" ::"n"(N) : "memory");
}
__device__ __forceinline__ void ldsm_x4(uint32_t addr, uint32_t& r0, uint32_t& r1, uint32_t& r2, uint32_t& r3) {
    asm volatile("ldmatrix.sync.aligned.m8n8.x4.shared.b16 {%0,%1,%2,%3}, [%4];"
                 : "=r"(r0), "=r"(r1), "=r"(r2), "=r"(r3) : "r"(addr) : "memory");
}
__device__ __forceinline__ void ldsm_x2(uint32_t addr, uint32_t& r0, uint32_t& r1) {
    asm volatile("ldmatrix.sync.aligned.m8n8.x2.shared.b16 {%0,%1}, [%2];" : "=r"(r0), "=r"(r1) : "r"(addr) : "memory");
}
__device__ __forceinline__ void stsm_x4(uint32_t addr, uint32_t r0, uint32_t r1, uint32_t r2, uint32_t r3) {
    asm volatile("stmatrix.sync.aligned.m8n8.x4.shared.b16 [%0], {%1,%2,%3,%4};"
                 ::"r"(addr), "r"(r0), "r"(r1), "r"(r2), "r"(r3) : "memory");
}
__device__ __forceinline__ uint4 lds128(uint32_t addr) {
    uint4 v;
    asm volatile("ld.shared.v4.u32 {%0,%1,%2,%3}, [%4];" : "=r"(v.x), "=r"(v.y), "=r"(v.z), "=r"(v.w) : "r"(addr) : "memory");
    return v;
}
__device__ __forceinline__ uint32_t lds32(uint32_t addr) {
    uint32_t a;
    asm volatile("ld.shared.u32 %0, [%1];" : "=r"(a) : "r"(addr) : "memory");
    return a;
}
__device__ __forceinline__ void sts32(uint32_t addr, uint32_t a) {
    asm volatile("st.shared.u32 [%0], %1;" ::"r"(addr), "r"(a) : "memory");
}
__device__ __forceinline__ void sts128(uint32_t addr, uint32_t a, uint32_t b, uint32_t c, uint32_t d) {
    asm volatile("st.shared.v4.u32 [%0], {%1,%2,%3,%4};" ::"r"(addr), "r"(a), "r"(b), "r"(c), "r"(d) : "memory");
}
__device__ __forceinline__ uint32_t hfma2_bf16(uint32_t a, uint32_t b, uint32_t c) {
    uint32_t d;
    asm("fma.rn.bf16x2 %0, %1, %2, %3;" : "=r"(d) : "r"(a), "r"(b), "r"(c));
    return d;
}
template <bool HI> __device__ __forceinline__ uint32_t hfma2_bf16_bcast(uint32_t a, uint32_t b, uint32_t c) {
    uint32_t d;
    if (HI)
        asm("{\n\t.reg .b16 a, b, c, d;\n\t.reg .b32 r, o;\n\tmov.b32 {a, b}, %2;\n\tmov.b32 {c, d}, %3;\n\t"
            "mov.b32 r, {b, b};\n\tmov.b32 o, {d, d};\n\tfma.rn.bf16x2 %0, %1, r, o;\n\t}" : "=r"(d) : "r"(a), "r"(b), "r"(c));
    else
        asm("{\n\t.reg .b16 a, b, c, d;\n\t.reg .b32 r, o;\n\tmov.b32 {a, b}, %2;\n\tmov.b32 {c, d}, %3;\n\t"
            "mov.b32 r, {a, a};\n\tmov.b32 o, {c, c};\n\tfma.rn.bf16x2 %0, %1, r, o;\n\t}" : "=r"(d) : "r"(a), "r"(b), "r"(c));
    return d;
}
__device__ __forceinline__ uint32_t hmul2_bf16(uint32_t a, uint32_t b) {
    uint32_t d;
    asm("mul.rn.bf16x2 %0, %1, %2;" : "=r"(d) : "r"(a), "r"(b));
    return d;
}
__device__ __forceinline__ uint32_t hadd2_bf16(uint32_t a, uint32_t b) {
    uint32_t d;
    asm("add.rn.bf16x2 %0, %1, %2;" : "=r"(d) : "r"(a), "r"(b));
    return d;
}
__device__ __forceinline__ float bf_lo(uint32_t v) { return __uint_as_float(v << 16); }
__device__ __forceinline__ float bf_hi(uint32_t v) { return __uint_as_float(v & 0xffff0000u); }
__device__ __forceinline__ uint32_t pack_bf16(float lo, float hi) {
    uint32_t d;
    asm("cvt.rn.bf16x2.f32 %0, %1, %2;" : "=r"(d) : "f"(hi), "f"(lo));
    return d;
}
__device__ __forceinline__ uint32_t pack_f16(float lo, float hi) {
    uint32_t d;
    asm("cvt.rn.f16x2.f32 %0, %1, %2;" : "=r"(d) : "f"(hi), "f"(lo));
    return d;
}
__device__ __forceinline__ uint32_t scale2h(uint32_t v, float s) {
    return pack_f16(bf_lo(v) * s, bf_hi(v) * s);
}
__device__ __forceinline__ uint32_t h2_to_bf2(uint32_t v) {
    uint32_t d;
    asm("{\n\t.reg .b16 l, h;\n\t.reg .f32 a, b;\n\tmov.b32 {l, h}, %1;\n\tcvt.f32.f16 a, l;\n\tcvt.f32.f16 b, h;\n\t"
        "cvt.rn.bf16x2.f32 %0, b, a;\n\t}" : "=r"(d) : "r"(v));
    return d;
}
__device__ __forceinline__ uint32_t bf2_to_h2(uint32_t y) { return (y & 0x7fff7fffu) * 7u + y; }
__device__ __forceinline__ uint32_t absmax2(uint32_t m, uint32_t v) { return __vmaxu2(m, v & 0x7fff7fffu); }
__device__ __forceinline__ void red_add_bf16x8(void* p, uint32_t a, uint32_t b, uint32_t c, uint32_t d, uint64_t pol) {
    asm volatile("red.global.add.noftz.L2::cache_hint.v4.bf16x2 [%0], {%1,%2,%3,%4}, %5;"
                 ::"l"(p), "r"(a), "r"(b), "r"(c), "r"(d), "l"(pol) : "memory");
}
__device__ __forceinline__ void wg_fence() { asm volatile("wgmma.fence.sync.aligned;" ::: "memory"); }
__device__ __forceinline__ void wg_commit() { asm volatile("wgmma.commit_group.sync.aligned;" ::: "memory"); }
template <int N> __device__ __forceinline__ void wg_wait() {
    asm volatile("wgmma.wait_group.sync.aligned %0;" ::"n"(N) : "memory");
}
template <int N> __device__ __forceinline__ void fence_regs(float (&d)[N]) {
#pragma unroll
    for (int i = 0; i < N; ++i) asm volatile("" : "+f"(d[i])::"memory");
}
template <int N> __device__ __forceinline__ void fence_regs(uint32_t (&d)[N]) {
#pragma unroll
    for (int i = 0; i < N; ++i) asm volatile("" : "+r"(d[i])::"memory");
}

template <int N> struct WH;
template <> struct WH<64> {
    static __device__ __forceinline__ void acc(uint32_t* d, uint32_t a0, uint32_t a1, uint32_t a2, uint32_t a3, uint64_t desc) {
        asm volatile("wgmma.mma_async.sync.aligned.m64n64k16.f16.f16.f16 {%0,%1,%2,%3,%4,%5,%6,%7,%8,%9,%10,%11,%12,%13,%14,%15}, "
                     "{%16,%17,%18,%19}, %20, 1, 1, 1, 1;"
                     : "+r"(d[0]), "+r"(d[1]), "+r"(d[2]), "+r"(d[3]), "+r"(d[4]), "+r"(d[5]), "+r"(d[6]), "+r"(d[7]), "+r"(d[8]), "+r"(d[9]), "+r"(d[10]), "+r"(d[11]), "+r"(d[12]), "+r"(d[13]), "+r"(d[14]), "+r"(d[15])
                     : "r"(a0), "r"(a1), "r"(a2), "r"(a3), "l"(desc) : "memory");
    }
    static __device__ __forceinline__ void first(uint32_t* d, uint32_t a0, uint32_t a1, uint32_t a2, uint32_t a3, uint64_t desc) {
        asm volatile("wgmma.mma_async.sync.aligned.m64n64k16.f16.f16.f16 {%0,%1,%2,%3,%4,%5,%6,%7,%8,%9,%10,%11,%12,%13,%14,%15}, "
                     "{%16,%17,%18,%19}, %20, 0, 1, 1, 1;"
                     : "=r"(d[0]), "=r"(d[1]), "=r"(d[2]), "=r"(d[3]), "=r"(d[4]), "=r"(d[5]), "=r"(d[6]), "=r"(d[7]), "=r"(d[8]), "=r"(d[9]), "=r"(d[10]), "=r"(d[11]), "=r"(d[12]), "=r"(d[13]), "=r"(d[14]), "=r"(d[15])
                     : "r"(a0), "r"(a1), "r"(a2), "r"(a3), "l"(desc) : "memory");
    }
};
template <> struct WH<96> {
    static __device__ __forceinline__ void acc(uint32_t* d, uint32_t a0, uint32_t a1, uint32_t a2, uint32_t a3, uint64_t desc) {
        asm volatile("wgmma.mma_async.sync.aligned.m64n96k16.f16.f16.f16 {%0,%1,%2,%3,%4,%5,%6,%7,%8,%9,%10,%11,%12,%13,%14,%15,%16,%17,%18,%19,%20,%21,%22,%23}, "
                     "{%24,%25,%26,%27}, %28, 1, 1, 1, 1;"
                     : "+r"(d[0]), "+r"(d[1]), "+r"(d[2]), "+r"(d[3]), "+r"(d[4]), "+r"(d[5]), "+r"(d[6]), "+r"(d[7]), "+r"(d[8]), "+r"(d[9]), "+r"(d[10]), "+r"(d[11]), "+r"(d[12]), "+r"(d[13]), "+r"(d[14]), "+r"(d[15]), "+r"(d[16]), "+r"(d[17]), "+r"(d[18]), "+r"(d[19]), "+r"(d[20]), "+r"(d[21]), "+r"(d[22]), "+r"(d[23])
                     : "r"(a0), "r"(a1), "r"(a2), "r"(a3), "l"(desc) : "memory");
    }
    static __device__ __forceinline__ void first(uint32_t* d, uint32_t a0, uint32_t a1, uint32_t a2, uint32_t a3, uint64_t desc) {
        asm volatile("wgmma.mma_async.sync.aligned.m64n96k16.f16.f16.f16 {%0,%1,%2,%3,%4,%5,%6,%7,%8,%9,%10,%11,%12,%13,%14,%15,%16,%17,%18,%19,%20,%21,%22,%23}, "
                     "{%24,%25,%26,%27}, %28, 0, 1, 1, 1;"
                     : "=r"(d[0]), "=r"(d[1]), "=r"(d[2]), "=r"(d[3]), "=r"(d[4]), "=r"(d[5]), "=r"(d[6]), "=r"(d[7]), "=r"(d[8]), "=r"(d[9]), "=r"(d[10]), "=r"(d[11]), "=r"(d[12]), "=r"(d[13]), "=r"(d[14]), "=r"(d[15]), "=r"(d[16]), "=r"(d[17]), "=r"(d[18]), "=r"(d[19]), "=r"(d[20]), "=r"(d[21]), "=r"(d[22]), "=r"(d[23])
                     : "r"(a0), "r"(a1), "r"(a2), "r"(a3), "l"(desc) : "memory");
    }
};

__device__ __forceinline__ void wgmma_stat(float (&d)[4], const uint32_t (&a)[4], uint64_t desc) {
    asm volatile("wgmma.mma_async.sync.aligned.m64n8k16.f32.bf16.bf16 {%0,%1,%2,%3}, {%4,%5,%6,%7}, %8, 0, 1, 1, 1;"
                 : "=f"(d[0]), "=f"(d[1]), "=f"(d[2]), "=f"(d[3]) : "r"(a[0]), "r"(a[1]), "r"(a[2]), "r"(a[3]), "l"(desc) : "memory");
}

__device__ __forceinline__ uint64_t make_desc(uint32_t addr, uint32_t lbo, uint32_t sbo) {
    return (uint64_t)((addr & 0x3FFFF) >> 4) | ((uint64_t)(lbo >> 4) << 16) | ((uint64_t)(sbo >> 4) << 32);
}

#define SCHED_FENCE() asm volatile("{\n\t.reg .pred p;\n\tsetp.ne.u32 p, %0, 0;\n\t@p exit;\n\t}" ::"r"(zero) : "memory")

__global__ void __launch_bounds__(NUM_THREADS, 1)
convnext_fused_kernel(const __grid_constant__ CUtensorMap xmap, const __grid_constant__ CUtensorMap w1map,
                      const __nv_bfloat16* __restrict__ dw, const __nv_bfloat16* __restrict__ w1,
                      const __nv_bfloat16* __restrict__ b1, const __nv_bfloat16* __restrict__ w2,
                      const __nv_bfloat16* __restrict__ b2, const __nv_bfloat16* __restrict__ gamma,
                      __nv_bfloat16* __restrict__ out, uint32_t zero) {
    extern __shared__ __align__(1024) uint8_t smem[];
    const uint32_t sbase = smem_u32(smem);
    const int tid = threadIdx.x;
    const int warp = __shfl_sync(0xffffffffu, tid >> 5, 0);
    const int lane = tid & 31;
    const int wg = warp >> 2, wr = warp & 3;
    const uint32_t bars = sbase + OFF_BAR;
    const int strip = blockIdx.x % NUM_STRIPS;
    const int band = blockIdx.x / NUM_STRIPS;
    const int dir = (band & 1) ? 1 : -1;
    const int ys = (band & 1) ? band * ROWS_PER_CTA - 1 : (band + 1) * ROWS_PER_CTA;

    auto load_row = [&](int j) {
        const uint32_t bar = bars + 8 * (BAR_ROW_FULL + (j & 3));
        const uint32_t dst = sbase + OFF_ROW + (j & 3) * ROW_BYTES;
        mbar_expect_tx(bar, 2 * HALF_BYTES);
        tma_load_3d(dst, &xmap, bar, 0, strip * STRIP_W - 1, ys + dir * j);
        tma_load_3d(dst + HALF_BOX, &xmap, bar, 0, strip * STRIP_W + 30, ys + dir * j);
    };
    auto load_w2 = [&](int s) {
        mbar_expect_tx(bars + 8 * (BAR_W2 + s), CH * HID / 2);
        bulk_load(sbase + OFF_W2 + s * (CH * HID / 2), w2 + s * (CH * HID / 4), CH * HID / 2, bars + 8 * (BAR_W2 + s));
    };
    if (warp == 11) {
        if (elect_one()) {
            asm volatile("prefetch.tensormap [%0];" ::"l"(reinterpret_cast<uint64_t>(&w1map)) : "memory");
#pragma unroll
            for (int s = 0; s < NUM_BARS; ++s)
                if (s < BAR_DONE || (s >= BAR_W1 && s <= BAR_DW)) mbar_init(bars + 8 * s, 1);
            asm volatile("fence.mbarrier_init.release.cluster;" ::: "memory");
        }
        __syncwarp();
        asm volatile("bar.arrive 2, %0;" ::"n"(NUM_THREADS) : "memory");
        if (elect_one()) {
#pragma unroll 1
            for (int s = 0; s < NCHUNK; ++s) {
                mbar_expect_tx(bars + 8 * (BAR_W1 + s), CH * NCH * 2);
                tma_load_2d(sbase + OFF_W1 + s * (CH * NCH * 2), &w1map, bars + 8 * (BAR_W1 + s), s * NCH, 0);
            }
            mbar_expect_tx(bars + 8 * BAR_DW, 9 * CH * 2);
            bulk_load(sbase + OFF_DW, dw, 9 * CH * 2, bars + 8 * BAR_DW);
            load_row(0);
            load_row(1);
            load_row(2);
#pragma unroll 1
            for (int s = 0; s < 4; ++s) load_w2(s);
            load_row(3);
        }
        __syncwarp();
        asm volatile("bar.sync 3, 64;" ::: "memory");
    } else if (warp == 9) {
        if (elect_one()) {
#pragma unroll
            for (int s = BAR_DONE; s < BAR_W1; ++s) mbar_init(bars + 8 * s, s < BAR_PRIME ? 8 : 4);
            mbar_init(bars + 8 * BAR_W1RDY, 4 * NMLP);
            mbar_init(bars + 8 * BAR_W2RDY, 8);
            asm volatile("mbarrier.arrive.shared::cta.b64 _, [%0], 4;" ::"r"(bars + 8 * BAR_DONE) : "memory");
        }
        __syncwarp();
        asm volatile("bar.arrive 3, 64;" ::: "memory");
    } else if (warp == 10) {
        if (elect_one()) asm volatile("prefetch.tensormap [%0];" ::"l"(reinterpret_cast<uint64_t>(&xmap)) : "memory");
    }

    if (wg == NMLP) {
        asm volatile("setmaxnreg.dec.sync.aligned.u32 128;");
        asm volatile("bar.sync 2, %0;" ::"n"(NUM_THREADS) : "memory");
        uint32_t w[3][3][3];
        {
            mbar_wait(bars + 8 * BAR_DW, 0);
            const uint32_t wp = sbase + OFF_DW + 48 * ((wr + (lane >> 2)) & 3) + 4 * (lane & 3) + 3 * (CH * 2);
#pragma unroll
            for (int s = 0; s < 3; ++s)
#pragma unroll
                for (int t = 0; t < 9; ++t) w[t / 3][t % 3][s] = lds32(wp + (t / 3 - 1) * dir * 3 * (CH * 2) + (t % 3) * (CH * 2) + s * 16);
        }
        const int ga = lane & 7, ja = lane >> 3;
        const uint32_t ip = sbase + OFF_ROW + (uint32_t)((ga >> 2) * HALF_OFF + (8 * (ga & 3) + ja) * (CH * 2) + 48 * ((wr + ga) & 3));
        const uint32_t op = sbase + OFF_A + (uint32_t)((ga >> 2) * A_HALF + (8 * (ga & 3) + ja) * A_PITCH + 48 * ((wr + ga) & 3));
        static_assert(NROW == 4 && NA == 2, "ring arithmetic");
        uint32_t P[2][3][8], f[10], c[8];
        auto load_window = [&](uint32_t a) {
            ldsm_x4(a, f[0], f[1], f[2], f[3]);
            ldsm_x4(a + 4 * (CH * 2), f[4], f[5], f[6], f[7]);
            ldsm_x2(a + 8 * (CH * 2), f[8], f[9]);
        };
        auto feed = [&](int e, int s, int i) {
#pragma unroll
            for (int o = i - 2; o <= i; ++o) {
                if (o < 0 || o > 7) continue;
                const int jx = i - o;
                if (jx == 0) {
                    asm volatile("fma.rn.bf16x2 %0, %3, %4, %1;\n\tfma.rn.bf16x2 %2, %3, %5, %2;\n\tmul.rn.bf16x2 %1, %3, %6;"
                                 : "=&r"(c[o]), "+r"(P[e][s][o]), "+r"(P[e ^ 1][s][o])
                                 : "r"(f[i]), "r"(w[2][0][s]), "r"(w[1][0][s]), "r"(w[0][0][s]));
                } else {
                    asm volatile("fma.rn.bf16x2 %0, %3, %4, %0;\n\tfma.rn.bf16x2 %2, %3, %5, %2;\n\tfma.rn.bf16x2 %1, %3, %6, %1;"
                                 : "+r"(c[o]), "+r"(P[e][s][o]), "+r"(P[e ^ 1][s][o])
                                 : "r"(f[i]), "r"(w[2][jx][s]), "r"(w[1][jx][s]), "r"(w[0][jx][s]));
                }
            }
        };
        __nv_bfloat16* xo = out + ((ys + dir) * IMG_W + strip * STRIP_W + wr * 16) * CH;
        const uint32_t xs = sbase + OFF_ROW + (wr >> 1) * HALF_OFF + ((wr & 1) * 16 + 1) * (CH * 2);
        mbar_wait(bars + 8 * BAR_ROW_FULL, 0);
#pragma unroll
        for (int r = 0; r < 2; ++r) {
            if (r == 1) {
                mbar_wait(bars + 8 * (BAR_ROW_FULL + 1), 0);
                if (elect_one()) bulk_store(xo, xs + ROW_BYTES, 16 * CH * 2);
                bulk_commit();
            }
#pragma unroll
            for (int s = 0; s < 3; ++s) {
                load_window(ip + r * ROW_BYTES + s * 16);
#pragma unroll
                for (int o = 0; o < 8; ++o) {
                    if (r == 1) P[0][s][o] = hfma2_bf16(f[o + 2], w[1][2][s], hfma2_bf16(f[o + 1], w[1][1][s], hfma2_bf16(f[o], w[1][0][s], P[0][s][o])));
                    P[r][s][o] = hfma2_bf16(f[o + 2], w[0][2][s], hfma2_bf16(f[o + 1], w[0][1][s], hmul2_bf16(f[o], w[0][0][s])));
                }
            }
        }
        __syncwarp();
        if (elect_one()) mbar_arrive(bars + 8 * BAR_PRIME);
        mbar_wait(bars + 8 * (BAR_ROW_FULL + 2), 0);
        load_window(ip + 2 * ROW_BYTES);
        const bool el = elect_one();
        uint32_t dbar = bars + 8 * BAR_DONE;
#pragma unroll 1
        for (int m = 0; m < ROWS_PER_CTA / 4; ++m) {
            const bool last = m + 1 == ROWS_PER_CTA / 4;
#pragma unroll
            for (int u = 0; u < 4; ++u) {
                const int j = 4 * m + u + 2;
                const int rs = (u + 2) & 3, ns = (u + 3) & 3;
                const uint32_t ebar = bars + 8 * (BAR_A_EMPTY + (u & 1)), rbar = bars + 8 * (BAR_ROW_FULL + ns);
                const uint32_t eph = ((u >> 1) & 1) ^ 1, rph = (m + (u >= 1)) & 1;
                xo += dir * IMG_W * CH;
                if (!(u == 3 && last)) {
                    if (elect_one()) bulk_store(xo, xs + rs * ROW_BYTES, 16 * CH * 2);
                }
                bulk_commit();
                bool ok = mbar_test(ebar, eph);
#pragma unroll
                for (int s = 0; s < 3; ++s) {
                    if (s == 2) ok = mbar_test(rbar, rph) || (u == 3 && last);
                    feed(u & 1, s, 0); feed(u & 1, s, 1); feed(u & 1, s, 2); feed(u & 1, s, 3);
                    if (s == 0) {
                        if (!ok) mbar_wait(ebar, eph);
                    }
                    const uint32_t nx = ip + (s == 2 ? ns : rs) * ROW_BYTES + ((s + 1) % 3) * 16;
                    const uint32_t ox = op + (u & 1) * A_BYTES + s * 16;
                    if (s < 2 || ok) ldsm_x4(nx, f[0], f[1], f[2], f[3]);
                    SCHED_FENCE();
                    feed(u & 1, s, 4); feed(u & 1, s, 5);
                    stsm_x4(ox, c[0], c[1], c[2], c[3]);
                    feed(u & 1, s, 6); feed(u & 1, s, 7);
                    ldsm_x4(nx + 4 * (CH * 2), f[4], f[5], f[6], f[7]);
                    SCHED_FENCE();
                    feed(u & 1, s, 8); feed(u & 1, s, 9);
                    stsm_x4(ox + 4 * A_PITCH, c[4], c[5], c[6], c[7]);
                    ldsm_x2(nx + 8 * (CH * 2), f[8], f[9]);
                    SCHED_FENCE();
                }
                bulk_wait<1>();
                __syncwarp();
                if (el) mbar_arrive(dbar);
                bulk_wait_read<0>();
                if (el) mbar_arrive(bars + 8 * (BAR_FREE + (u & 1)));
                dbar = dbar == bars + 8 * (BAR_DONE + NMLP - 1) ? bars + 8 * BAR_DONE : dbar + 8;
                if ((wr == u && !last) || (u == 0 && m == 0 && wr == 1)) {
                    mbar_wait(bars + 8 * (BAR_FREE + (u & 1)), (u >> 1) & 1);
                    if (elect_one()) load_row(u == 0 ? j + 4 - wr : j + 4);
                }
                if (!ok) {
                    mbar_wait(rbar, rph);
                    load_window(ip + ns * ROW_BYTES);
                }
            }
        }
    } else {
        const int g = lane >> 2, q = lane & 3;
        const uint4 r95 = __ldg(reinterpret_cast<const uint4*>(w1 + 95 * HID + (warp >> 1) * NCH + (lane & 7) * 8));
        const uint4 bb = __ldg(reinterpret_cast<const uint4*>(b1 + (warp >> 1) * NCH + (lane & 7) * 8));
        uint4 gm[3];
#pragma unroll
        for (int jj = 0; jj < 3; ++jj) gm[jj] = __ldg(reinterpret_cast<const uint4*>(gamma + jj * 32 + q * 8));
        uint32_t b2v = 0, g2v = 0;
        if (tid >= 128 && tid < 128 + CH / 2) {
            b2v = __ldg(reinterpret_cast<const uint32_t*>(b2) + tid - 128);
            g2v = __ldg(reinterpret_cast<const uint32_t*>(gamma) + tid - 128);
        }
        auto transform_w2 = [&](int s, int pass) {
            const uint32_t w2b = sbase + OFF_W2 + (warp - 4) * 6 * (8 * CH * 2);
            const float up = __uint_as_float((uint32_t)(127 + s) << 23), sc = up * GELU_INV2A;
            uint32_t gh[12];
#pragma unroll
            for (int e = 0; e < 12; ++e) {
                const uint32_t gv = (e & 3) == 0 ? gm[e / 4].x : (e & 3) == 1 ? gm[e / 4].y : (e & 3) == 2 ? gm[e / 4].z : gm[e / 4].w;
                gh[e] = pack_bf16(bf_lo(gv) * sc * 0x1p-112f, bf_hi(gv) * sc * 0x1p-112f);
            }
            if (tid < 128 + CH / 2) {
                const uint32_t v2 = pack_f16(bf_lo(b2v) * bf_lo(g2v) * up, bf_hi(b2v) * bf_hi(g2v) * up);
                const uint32_t a = sbase + OFF_B2I + (((tid >> 4) & 3) * 2 + ((tid >> 1) & 1)) * 128 + ((tid >> 2) & 3) * 16 + (tid & 1) * 8;
                sts32(a, v2); sts32(a + 4, v2);
                sts32(a + 64, 0); sts32(a + 68, 0);
            }
            mbar_wait(bars + 8 * (BAR_W2 + (warp >> 1) - 2), pass);
            uint4 v[3];
#pragma unroll
            for (int jj = 0; jj < 3; ++jj) v[jj] = lds128(w2b + g * (CH * 2) + jj * 64 + q * 16);
            uint32_t mu = 0, ms = 0;
#pragma unroll 1
            for (int i = 0; i < 6; ++i) {
                uint32_t o[12];
#pragma unroll
                for (int jj = 0; jj < 3; ++jj) {
                    mu = __vmaxu2(__vmaxu2(mu, v[jj].x), v[jj].y); mu = __vmaxu2(__vmaxu2(mu, v[jj].z), v[jj].w);
                    ms = __vmaxs2(__vmaxs2(ms, v[jj].x), v[jj].y); ms = __vmaxs2(__vmaxs2(ms, v[jj].z), v[jj].w);
                    o[jj * 4 + 0] = hmul2_bf16(v[jj].x, gh[jj * 4 + 0]);
                    o[jj * 4 + 1] = hmul2_bf16(v[jj].y, gh[jj * 4 + 1]);
                    o[jj * 4 + 2] = hmul2_bf16(v[jj].z, gh[jj * 4 + 2]);
                    o[jj * 4 + 3] = hmul2_bf16(v[jj].w, gh[jj * 4 + 3]);
                    if (i < 5) v[jj] = lds128(w2b + (i + 1) * (8 * CH * 2) + g * (CH * 2) + jj * 64 + q * 16);
                }
                __syncwarp();
#pragma unroll
                for (int e = 0; e < 12; ++e) o[e] = bf2_to_h2(o[e]);
#pragma unroll
                for (int jj = 0; jj < 3; ++jj)
                    stsm_x4(w2b + i * (8 * CH * 2) + jj * 512 + lane * 16, o[jj * 4], o[jj * 4 + 1], o[jj * 4 + 2], o[jj * 4 + 3]);
            }
            mu = __vmaxu2(mu & 0x7fff7fffu, ms);
            return __reduce_max_sync(0xffffffffu, max(mu & 0xffffu, mu >> 16));
        };
        if (warp != 11) asm volatile("bar.sync 2, %0;" ::"n"(NUM_THREADS) : "memory");
        asm volatile("setmaxnreg.inc.sync.aligned.u32 128;");
        {
            const int box = warp >> 1, cc = lane & 7, k0 = (warp & 1) * 48 + (lane >> 3);
            constexpr uint32_t DN = 0x07800780u;
            if (tid < 16) {
                const uint32_t v = tid < 8 ? 0x3F80u : 0x3F800000u;
                sts128(sbase + OFF_SEL + tid * 16, v, v, v, v);
            }
            const uint32_t m[4] = {hmul2_bf16(r95.x, DN | 0x80008000u), hmul2_bf16(r95.y, DN | 0x80008000u),
                                   hmul2_bf16(r95.z, DN | 0x80008000u), hmul2_bf16(r95.w, DN | 0x80008000u)};
            const uint32_t tb[4] = {scale2h(bb.x, GELU_A), scale2h(bb.y, GELU_A), scale2h(bb.z, GELU_A), scale2h(bb.w, GELU_A)};
            uint32_t mx = absmax2(absmax2(absmax2(absmax2(0, hmul2_bf16(bb.x, DN)), hmul2_bf16(bb.y, DN)), hmul2_bf16(bb.z, DN)), hmul2_bf16(bb.w, DN));
            uint32_t mg = 0;
#pragma unroll
            for (int jj = 0; jj < 3; ++jj) mg = absmax2(absmax2(absmax2(absmax2(mg, gm[jj].x), gm[jj].y), gm[jj].z), gm[jj].w);
            mg = __reduce_max_sync(0xffffffffu, max(mg & 0xffffu, mg >> 16));
            if (warp == 4 || warp == 5) {
                const uint32_t mb = __reduce_max_sync(0xffffffffu, max(b2v & 0x7fffu, (b2v >> 16) & 0x7fffu));
                if (lane == 0) sts32(sbase + OFF_MAX + 32 + warp * 4, mb);
            }
            const uint32_t wb = sbase + OFF_W1 + box * (CH * NCH * 2);
            const uint32_t wa[2] = {wb + k0 * 128 + ((cc ^ (k0 & 7)) << 4), wb + (k0 + 4) * 128 + ((cc ^ ((k0 + 4) & 7)) << 4)};
            mbar_wait(bars + 8 * (BAR_W1 + box), 0);
            uint4 u[2] = {lds128(wa[0]), lds128(wa[1])};
#pragma unroll 1
            for (int i = 0; i < 6; ++i) {
                uint32_t t[2][4];
#pragma unroll
                for (int e = 0; e < 2; ++e) {
                    t[e][0] = hfma2_bf16(u[e].x, DN, m[0]); t[e][1] = hfma2_bf16(u[e].y, DN, m[1]);
                    t[e][2] = hfma2_bf16(u[e].z, DN, m[2]); t[e][3] = hfma2_bf16(u[e].w, DN, m[3]);
                    if (i < 5) u[e] = lds128(wa[e] + (i + 1) * 1024);
#pragma unroll
                    for (int x = 0; x < 4; ++x) {
                        mx = absmax2(mx, t[e][x]);
                        t[e][x] = bf2_to_h2(t[e][x]);
                    }
                }
                sts128(wa[0] + i * 1024, t[0][0], t[0][1], t[0][2], t[0][3]);
                sts128(wa[1] + i * 1024, t[1][0], t[1][1], t[1][2], t[1][3]);
            }
            if (k0 + 44 == 95) sts128(wa[1] + 5 * 1024, tb[0], tb[1], tb[2], tb[3]);
            const uint32_t m1w = __reduce_max_sync(0xffffffffu, max(mx & 0xffffu, mx >> 16));
            if (lane == 0) sts32(sbase + OFF_MAX + warp * 4, m1w << 16);
            asm volatile("fence.proxy.async.shared::cta;" ::: "memory");
            __syncwarp();
            if (elect_one()) mbar_arrive(bars + 8 * BAR_W1RDY);
            if (wg > 0) {
                const uint32_t m2w = transform_w2(0, 0);
                if (lane == 0) sts32(sbase + OFF_MAX + warp * 4, m2w | (m1w << 16));
                asm volatile("fence.proxy.async.shared::cta;" ::: "memory");
                mbar_wait(bars + 8 * BAR_W1RDY, 0);
                asm volatile("bar.sync 1, 256;" ::: "memory");
                const uint32_t mm = lane < 14 ? lds32(sbase + OFF_MAX + lane * 4) : 0;
                const uint32_t m1 = __reduce_max_sync(0xffffffffu, lane < 12 ? mm >> 16 : 0);
                const uint32_t m2 = __reduce_max_sync(0xffffffffu, lane < 12 ? mm & 0xffffu : 0), mb = __reduce_max_sync(0xffffffffu, lane < 12 ? 0 : mm);
                const int e1 = max((int)(m1 >> 7), 1) - 14, eg = (int)(mg >> 7) - 126, ew = (int)(m2 >> 7) - 126;
                const int e2 = ew + eg + 1, eb = (int)(mb >> 7) - 126 + eg;
                int s = min(min(-1 - e1 - e2, 14 - eb), 14 - e2);
                if (s >= 0 && s <= 12 && e2 >= -9 && eg >= -9) s = 0;
                s = min(max(s, -120), min(120, 120 - eg));
                if (s != 0) {
                    if ((warp & 1) == 0 && elect_one()) load_w2((warp >> 1) - 2);
                    transform_w2(s, 1);
                    asm volatile("fence.proxy.async.shared::cta;" ::: "memory");
                }
                if (tid == 128) sts32(sbase + OFF_MAX + 64, (uint32_t)(127 - s) * 0x00800080u);
                __syncwarp();
                if (elect_one()) mbar_arrive(bars + 8 * BAR_W2RDY);
            } else if (wr == 0) {
                mbar_wait(bars + 8 * BAR_PRIME, 0);
                if (elect_one()) load_row(4);
            }
        }
        const uint64_t descW1 = make_desc(sbase + OFF_W1, CH * NCH * 2, 1024) | (1ull << 62);
        const uint64_t descW2 = make_desc(sbase + OFF_W2, (CH / 8) * 128, 128);
        const uint64_t descW2r = (make_desc(0, 0, 128) & ~0xffffffffull) |
                                __shfl_sync(0xffffffffu, (uint32_t)make_desc(sbase + OFF_W2, (CH / 8) * 128, 128), 0);
        const uint64_t descS = make_desc(sbase + OFF_SEL, 128, 128);
        uint32_t la = sbase + OFF_A + (wg & 1) * A_BYTES + wr * 16 * A_PITCH + (wr >> 1) * 64 +
                      (uint32_t)(((lane & 7) + ((lane >> 3) & 1) * 8) * A_PITCH + (lane >> 4) * 16);

        uint32_t acc2[24];
        uint32_t h[2][NCH / 4];
        uint32_t a1[6][4];
        uint32_t yr[6][4];
        uint32_t pp[4];
        float st[4];

        auto load_a = [&](int k0, int k1) {
#pragma unroll
            for (int kb = k0; kb < k1; ++kb) ldsm_x4(la + kb * 32, yr[kb][0], yr[kb][1], yr[kb][2], yr[kb][3]);
        };
        auto partial_a = [&](int i) {
            uint32_t s = hadd2_bf16(hadd2_bf16(hadd2_bf16(yr[0][i], yr[1][i]), hadd2_bf16(yr[2][i], yr[3][i])), hadd2_bf16(yr[4][i], yr[5][i]));
            uint32_t v = hmul2_bf16(yr[0][i], yr[0][i]);
#pragma unroll
            for (int kb = 1; kb < 6; ++kb) v = hfma2_bf16(yr[kb][i], yr[kb][i], v);
            if (i >= 2) { s = hadd2_bf16(s, pp[i & 1]); v = hadd2_bf16(v, pp[2 + (i & 1)]); }
            asm volatile("" : "+r"(s), "+r"(v));
            pp[i & 1] = s; pp[2 + (i & 1)] = v;
        };
        uint32_t sel95 = q == 3 ? 0x7610 : 0x3210;
        asm volatile("" : "+r"(sel95));
        auto norm_a = [&]() {
            constexpr float K = GELU_A * 0x1p-112f, SQ = 9.797958971132712f;
            float m0 = st[0] * (-1.f / CH), m1 = st[2] * (-1.f / CH);
            float r0, r1;
            asm("rsqrt.approx.ftz.f32 %0, %1;" : "=f"(r0) : "f"(fmaf(m0, st[0], st[1]) + CH * 1e-5f));
            asm("rsqrt.approx.ftz.f32 %0, %1;" : "=f"(r1) : "f"(fmaf(m1, st[2], st[3]) + CH * 1e-5f));
            const uint32_t rp = pack_bf16(r0 * (K * SQ), r1 * (K * SQ));
            const float o0 = m0 * bf_lo(rp), o1 = m1 * bf_hi(rp);
            const uint32_t op = pack_bf16(o0, o1);
            const bool easy = (fabsf(o0) < 0.5f * K) & (fabsf(o1) < 0.5f * K) & (fminf(r0, r1) > 0x1p-12f);
            if (__all_sync(0xffffffffu, easy)) {
#pragma unroll
                for (int kb = 0; kb < 6; ++kb)
#pragma unroll
                    for (int i = 0; i < 4; ++i)
                        a1[kb][i] = bf2_to_h2((i & 1) ? hfma2_bf16_bcast<true>(yr[kb][i], rp, op) : hfma2_bf16_bcast<false>(yr[kb][i], rp, op));
            } else {
                float s0[2] = {0.f, 0.f}, s1[2] = {0.f, 0.f}, v0[2] = {0.f, 0.f}, v1[2] = {0.f, 0.f};
#pragma unroll
                for (int kb = 0; kb < 6; ++kb)
#pragma unroll
                    for (int i = 0; i < 2; ++i) {
                        float a = bf_lo(yr[kb][2 * i]), b = bf_hi(yr[kb][2 * i]);
                        s0[0] += a; v0[0] = fmaf(a, a, v0[0]); s0[1] += b; v0[1] = fmaf(b, b, v0[1]);
                        a = bf_lo(yr[kb][2 * i + 1]); b = bf_hi(yr[kb][2 * i + 1]);
                        s1[0] += a; v1[0] = fmaf(a, a, v1[0]); s1[1] += b; v1[1] = fmaf(b, b, v1[1]);
                    }
                float sa = s0[0] + s0[1], sb = s1[0] + s1[1], va = v0[0] + v0[1], vb = v1[0] + v1[1];
                sa += __shfl_xor_sync(0xffffffffu, sa, 1); sb += __shfl_xor_sync(0xffffffffu, sb, 1);
                va += __shfl_xor_sync(0xffffffffu, va, 1); vb += __shfl_xor_sync(0xffffffffu, vb, 1);
                sa += __shfl_xor_sync(0xffffffffu, sa, 2); sb += __shfl_xor_sync(0xffffffffu, sb, 2);
                va += __shfl_xor_sync(0xffffffffu, va, 2); vb += __shfl_xor_sync(0xffffffffu, vb, 2);
                m0 = sa * (1.f / CH); m1 = sb * (1.f / CH);
                asm("rsqrt.approx.ftz.f32 %0, %1;" : "=f"(r0) : "f"(fmaxf(fmaf(-m0, m0, va * (1.f / CH)), 0.f) + 1e-5f));
                asm("rsqrt.approx.ftz.f32 %0, %1;" : "=f"(r1) : "f"(fmaxf(fmaf(-m1, m1, vb * (1.f / CH)), 0.f) + 1e-5f));
                r0 *= GELU_A; r1 *= GELU_A;
                const float p0 = -m0 * r0, p1 = -m1 * r1;
#pragma unroll
                for (int kb = 0; kb < 6; ++kb)
#pragma unroll
                    for (int i = 0; i < 4; ++i) {
                        const float r = (i & 1) ? r1 : r0, o = (i & 1) ? p1 : p0;
                        a1[kb][i] = pack_f16(fmaf(bf_lo(yr[kb][i]), r, o), fmaf(bf_hi(yr[kb][i]), r, o));
                    }
            }
            a1[5][2] = __byte_perm(a1[5][2], 0x3C000000u, sel95);
            a1[5][3] = __byte_perm(a1[5][3], 0x3C000000u, sel95);
        };
        auto gemm1 = [&](int c, int k0, int k1) {
#pragma unroll
            for (int kk = k0; kk < k1; ++kk) {
                if (kk == 0) WH<NCH>::first(h[c & 1], a1[0][0], a1[0][1], a1[0][2], a1[0][3], descW1 + (uint64_t)(c * 768));
                else WH<NCH>::acc(h[c & 1], a1[kk][0], a1[kk][1], a1[kk][2], a1[kk][3], descW1 + (uint64_t)(c * 768 + kk * 128));
            }
        };
        auto gemm2 = [&](int c, int k0, int k1) {
#pragma unroll
            for (int kk = k0; kk < k1; ++kk)
                WH<96>::acc(acc2, h[c & 1][kk * 4], h[c & 1][kk * 4 + 1], h[c & 1][kk * 4 + 2], h[c & 1][kk * 4 + 3],
                            (c * 4 + kk < NRES ? descW2r : descW2) + (uint64_t)(((c * (NCH / 8) + 2 * kk) * (CH / 8)) * 8));
        };
        uint32_t b2a = sbase + OFF_B2I + q * 16;
        asm volatile("" : "+r"(b2a));

        mbar_wait(bars + 8 * BAR_W1RDY, 0);
        static_assert((OFF_BAR + 8 * BAR_A_EMPTY) % 16 == 0 && (NMLP & 1), "the conv-tile slot alternates");
        const uint32_t nbar = bars + 8 * (BAR_DONE + wg), tbar = bars + 8 * (BAR_DONE + (wg + 1) % NMLP);
        uint32_t ebar = bars + 8 * (BAR_A_EMPTY + (wg & 1)), nph = 0;
        int astep = __shfl_sync(0xffffffffu, (wg & 1) ? -A_BYTES : A_BYTES, 0);
        mbar_wait(nbar, 0);
        load_a(0, 6);
#pragma unroll
        for (int i = 0; i < 4; ++i) partial_a(i);
        wg_fence();
        wgmma_stat(st, pp, descS);
        wg_commit();
        __syncwarp();
        if (elect_one()) {
            mbar_arrive(ebar);
            mbar_arrive(tbar);
        }
        wg_wait<0>();
        fence_regs(st);
        norm_a();
        wg_fence();
        gemm1(0, 0, 6);
        wg_commit();
        mbar_wait(bars + 8 * BAR_W2RDY, 0);
        const uint32_t oscale = __shfl_sync(0xffffffffu, lds32(sbase + OFF_MAX + 64), 0);
#define Y(i) yr[2 * ((i) / 8) + ((i) & 1)][((i) / 2) % 4]
#pragma unroll
        for (int m = 0; m < 6; ++m) {
            const uint4 v = lds128(b2a + m * 128);
            Y(4 * m) = Y(4 * m + 1) = hmul2_bf16(h2_to_bf2(v.x), oscale);
            Y(4 * m + 2) = Y(4 * m + 3) = hmul2_bf16(h2_to_bf2(v.z), oscale);
        }
        wg_wait<0>();
        b2a += 64;
        __nv_bfloat16* optr = out + ((ys + dir * (wg + 1)) * IMG_W + strip * STRIP_W + wr * 16 + g) * CH + q * 8;
        auto red_y = [&](int i, uint64_t pol) {
            red_add_bf16x8(optr + (i % 2) * 8 * CH + (i / 2) * 32, yr[i][0], yr[i][1], yr[i][2], yr[i][3], pol);
        };
        uint64_t rpol = policy_evict_normal();
        long long ostep = 0;
#pragma unroll 1
        for (int t = wg;; t += NMLP) {
            const bool more = t + NMLP < ROWS_PER_CTA;
            bool ready = true;
            SCHED_FENCE();
            constexpr int P = NCH / 4, NP = HID / 4;
            uint32_t zz[2];
            uint16_t t0[LAG], t1[LAG];
#pragma unroll
            for (int G = 0; G <= NP + LAG; ++G) {
                const int ca = G / P, gp = G % P;
                if (G == TESTPOS) ready = mbar_test(nbar, nph);
                if (G == PICKPOS && !ready) mbar_wait(nbar, nph);
                if (gp == 0 && ca >= 1 && G < NP) { wg_wait<1>(); fence_regs(h[ca & 1]); }
                if (G == PICKPOS) load_a(0, NFREE);
                if (G == PICKPOS && astep != 0) load_a(NFREE, 6);
                if (ca + 1 < NCHUNK && gp == (ca == 0 ? 1 : G1PA)) {
                    if (ca > 0) wg_wait<0>();
                    wg_fence();
                    gemm1(ca + 1, 0, 3);
                }
                if (ca + 1 < NCHUNK && gp == (ca == 0 ? 3 : G1PB)) {
                    wg_fence();
                    gemm1(ca + 1, 3, 6);
                    wg_commit();
                }
                if (ca < NCHUNK && gp == G2PA) {
                    fence_regs(h[ca & 1]);
                    wg_fence();
                    if (G == STATPOS) wgmma_stat(st, pp, descS);
                    gemm2(ca, 0, 2);
                    wg_commit();
                }
                if (ca >= 1 && gp == G2PB - P) {
                    fence_regs(h[(ca - 1) & 1]);
                    wg_fence();
                    gemm2(ca - 1, 2, 4);
                    wg_commit();
                }
                if (G == INITPOS) {
#pragma unroll
                    for (int m = 0; m < 6; ++m) {
                        const uint4 v = lds128(b2a + m * 128);
                        acc2[4 * m] = v.x; acc2[4 * m + 1] = v.y; acc2[4 * m + 2] = v.z; acc2[4 * m + 3] = v.w;
                    }
                }
                if (G == RELPOS) {
                    __syncwarp();
                    if (lane == 0) mbar_arrive(ebar);
                }
                if (G >= REDPOS && G < REDPOS + 6 * REDSTEP && (G - REDPOS) % REDSTEP == 0) red_y((G - REDPOS) / REDSTEP, rpol);
                if (G == UPDPOS) {
                    asm volatile("add.u32 %0, %0, %1;" : "+r"(la) : "r"(astep));
                    astep = -astep;
                    asm volatile("and.b32 %0, %0, 0xffffffbf;" : "+r"(b2a));
                    ebar = more ? ebar ^ 8 : bars + 8 * BAR_DW;
                    nph ^= more;
                    asm volatile("add.u64 %0, %0, %1;" : "+l"(optr) : "l"(ostep));
                    ostep = (long long)dir * (NMLP * IMG_W * CH * 2);
                    rpol = policy_evict_first();
                }
                if (G >= STATPOS - 4 && G < STATPOS) partial_a(G - (STATPOS - 4));
                int e = G - LAG;
                if (e >= 0 && e < NP) {
                    uint32_t& v = h[(e / P) & 1][e % P];
                    uint32_t o;
                    asm volatile("{\n\t.reg .b32 t;\n\tmov.b32 t, {%2, %3};\n\tfma.rn.f16x2 %0, %1, t, %1;\n\t}"
                                 : "=r"(o) : "r"(v), "h"(t0[e % LAG]), "h"(t1[e % LAG]));
                    v = o;
                }
                e = G - 1;
                if (e >= 0 && e < NP)
                    asm volatile("{\n\t.reg .b16 l, h;\n\tmov.b32 {l, h}, %2;\n\ttanh.approx.f16 %0, l;\n\ttanh.approx.f16 %1, h;\n\t}"
                                 : "=h"(t0[e % LAG]), "=h"(t1[e % LAG]) : "r"(zz[e & 1]));
                if (G < NP)
                    asm volatile("{\n\t.reg .b32 p;\n\tfma.rn.f16x2 p, %1, %1, %2;\n\tmul.rn.f16x2 %0, %1, p;\n\t}"
                                 : "=r"(zz[G & 1]) : "r"(h[ca & 1][gp]), "r"(0x40D940D9u));
                SCHED_FENCE();
            }
            if (!more) break;
            wg_wait<1>();
            fence_regs(st);
            norm_a();
            if (lane == 0) mbar_arrive(tbar);
            wg_fence();
            gemm1(0, 0, 6);
            wg_commit();
            SCHED_FENCE();
            wg_wait<1>();
            fence_regs(acc2);
#pragma unroll
            for (int i = 0; i < 24; ++i) Y(i) = h2_to_bf2(acc2[i]);
            if (oscale != 0x3F803F80u) {
#pragma unroll
                for (int i = 0; i < 24; ++i) Y(i) = hmul2_bf16(Y(i), oscale);
            }
            wg_wait<0>();
        }
        wg_wait<0>();
        fence_regs(acc2);
#pragma unroll
        for (int i = 0; i < 24; ++i) Y(i) = hmul2_bf16(h2_to_bf2(acc2[i]), oscale);
#pragma unroll
        for (int i = 0; i < 6; ++i) red_y(i, policy_evict_normal());
    }
}

typedef CUresult (*PFN_encodeTiled)(CUtensorMap*, CUtensorMapDataType, cuuint32_t, void*, const cuuint64_t*,
                                    const cuuint64_t*, const cuuint32_t*, const cuuint32_t*, CUtensorMapInterleave,
                                    CUtensorMapSwizzle, CUtensorMapL2promotion, CUtensorMapFloatOOBfill);

}

extern "C" void kernel_launch(void* const* d_in, const int* in_sizes, int n_in, void* d_out, int out_size) {
    const __nv_bfloat16* x = (const __nv_bfloat16*)d_in[0];
    const __nv_bfloat16* dw = (const __nv_bfloat16*)d_in[1];
    const __nv_bfloat16* w1 = (const __nv_bfloat16*)d_in[2];
    const __nv_bfloat16* b1 = (const __nv_bfloat16*)d_in[3];
    const __nv_bfloat16* w2 = (const __nv_bfloat16*)d_in[4];
    const __nv_bfloat16* b2 = (const __nv_bfloat16*)d_in[5];
    const __nv_bfloat16* gamma = (const __nv_bfloat16*)d_in[6];
    __nv_bfloat16* out = (__nv_bfloat16*)d_out;

    static PFN_encodeTiled encode = nullptr;
    if (!encode) {
        void* fn = nullptr;
        cudaDriverEntryPointQueryResult qres;
        cudaGetDriverEntryPoint("cuTensorMapEncodeTiled", &fn, cudaEnableDefault, &qres);
        encode = (PFN_encodeTiled)fn;
        cudaFuncSetAttribute(convnext_fused_kernel, cudaFuncAttributeMaxDynamicSharedMemorySize, SMEM_BYTES);
    }
    CUtensorMap xmap, w1map;
    cuuint64_t gdim[3] = {CH, IMG_W, IMG_H};
    cuuint64_t gstr[2] = {CH * 2, (cuuint64_t)IMG_W * CH * 2};
    cuuint32_t box[3] = {CH, HALF_W, 1};
    cuuint32_t estr[3] = {1, 1, 1};
    encode(&xmap, CU_TENSOR_MAP_DATA_TYPE_BFLOAT16, 3, (void*)x, gdim, gstr, box, estr, CU_TENSOR_MAP_INTERLEAVE_NONE,
           CU_TENSOR_MAP_SWIZZLE_NONE, CU_TENSOR_MAP_L2_PROMOTION_L2_128B, CU_TENSOR_MAP_FLOAT_OOB_FILL_NONE);
    cuuint64_t wdim[2] = {HID, CH};
    cuuint64_t wstr[1] = {HID * 2};
    cuuint32_t wbox[2] = {NCH, CH};
    encode(&w1map, CU_TENSOR_MAP_DATA_TYPE_BFLOAT16, 2, (void*)w1, wdim, wstr, wbox, estr, CU_TENSOR_MAP_INTERLEAVE_NONE,
           CU_TENSOR_MAP_SWIZZLE_128B, CU_TENSOR_MAP_L2_PROMOTION_L2_256B, CU_TENSOR_MAP_FLOAT_OOB_FILL_NONE);

    convnext_fused_kernel<<<NUM_CTAS, NUM_THREADS, SMEM_BYTES>>>(xmap, w1map, dw, w1, b1, w2, b2, gamma, out, 0u);
}
```
